```python
import torch

def _softmax(x, axis=-1):
    return torch.softmax(x, dim=axis)
def _gelu(x):
    return torch.nn.functional.gelu(x, approximate="tanh")
def _silu(x):
    return torch.nn.functional.silu(x)
def _sigmoid(x):
    return torch.sigmoid(x)
def _layernorm(x, axis=-1, eps=1e-5):
    m = x.mean(dim=axis, keepdim=True)
    v = x.var(dim=axis, keepdim=True, unbiased=False)
    return (x - m) / torch.sqrt(v + eps)
def _scatter_add(tgt, idx, src, axis=0):
    return tgt.clone().index_add_(axis, idx, src)
def _segment_sum(src, seg, n):
    out = torch.zeros((n,) + src.shape[1:], dtype=src.dtype)
    return out.index_add_(0, seg, src)
def _pad(x, pw):
    flat = tuple(v for pair in reversed(pw) for v in pair)
    return torch.nn.functional.pad(x, flat)

kernel_name = 'parallel_sum__linear_attn_block__dense_activation_mish__prompt'

def setup_inputs():

    _w = (lambda a: (lambda t: t.to(torch.bfloat16) if t.is_floating_point() else t)(torch.as_tensor(a)))
    def _A_setup():
        B, S, D = 1, 2048, 512
        return {
            "x": _w((lambda *s: torch.randn(*s, dtype=torch.bfloat16) * 0.05)(B, S, D)),
            "wqkv": _w((lambda *s: torch.randn(*s, dtype=torch.bfloat16) * 0.1)(D, 3 * D)),
            "wo": _w((lambda *s: torch.randn(*s, dtype=torch.bfloat16) * 0.05)(D, D)),
        }
    _A_in = _A_setup()

    def _B_setup():
        B, S, D, F = 1, 2048, 512, 1376
        return {
            "x": _w((lambda *s: torch.randn(*s, dtype=torch.bfloat16) * 0.05)(B, S, D)),
            "w1": _w((lambda *s: torch.randn(*s, dtype=torch.bfloat16) * 0.8)(D, F) * (D ** -0.5)),
            "b1": _w((lambda *s: torch.randn(*s, dtype=torch.bfloat16) * 0.4)(F)),
            "w2": _w((lambda *s: torch.randn(*s, dtype=torch.bfloat16) * 0.1)(F, D) * (F ** -0.5)),
        }
    _B_in = _B_setup()

    return {
        "A_x": _A_in["x"],
        "A_wqkv": _A_in["wqkv"],
        "A_wo": _A_in["wo"],
        "B_x": _B_in["x"],
        "B_w1": _B_in["w1"],
        "B_b1": _B_in["b1"],
        "B_w2": _B_in["w2"],
    }

def reference(A_x, A_wqkv, A_wo, B_x, B_w1, B_b1, B_w2):
    def _A_ref(x, wqkv, wo):
        B, S, D = x.shape
        H = 32; Dh = D // H
        qkv = (lambda x, *d: x.permute(*d))((x @ wqkv).reshape(B, S, 3, H, Dh), 2, 0, 3, 1, 4)
        q, k, v = qkv[0], qkv[1], qkv[2]
        phi = lambda t: torch.where(t > 0, t + 1, torch.exp(t)) + 1e-6
        pq, pk = phi(q), phi(k)
        kv = torch.einsum("bhsd,bhse->bhde", pk, v)
        z = torch.einsum("bhsd->bhd", pk)
        num = torch.einsum("bhqd,bhde->bhqe", pq, kv)
        den = torch.einsum("bhqd,bhd->bhq", pq, z)[..., None] + 1e-6
        o = num / den
        return (lambda x, *d: x.permute(*d))(o, 0, 2, 1, 3).reshape(B, S, D) @ wo

    def _B_ref(x, w1, b1, w2):
        h = torch.einsum("bsd,df->bsf", x, w1) + b1
        sp = torch.log1p(torch.exp(-torch.abs(h))) + torch.where(h > 0, h, torch.zeros_like(h))
        act = h * torch.tanh(sp)
        return torch.einsum("bsf,fd->bsd", act, w2)

    x = A_x
    xn = _layernorm(x, axis=-1)
    return x + _A_ref(xn, A_wqkv, A_wo) + _B_ref(xn, B_w1, B_b1, B_w2)
```

```cpp
#include <cuda_runtime.h>
#include <cuda.h>
#include <cuda_bf16.h>
#include <stdint.h>

namespace {

constexpr int S_ = 2048, D_ = 512, F_ = 1376, FS = 176;

constexpr uint32_t XS = 0;
constexpr uint32_t RING = 131072;
constexpr uint32_t MISC = 229376;
constexpr uint32_t B_FULL = MISC, B_EMPTY = MISC + 48, B_XFULL = MISC + 96;
constexpr uint32_t B_KVPART = MISC + 160, B_KVRDY = MISC + 168, B_CSPART = MISC + 176, B_CSRDY = MISC + 184, B_X2FREE = MISC + 192;
constexpr uint32_t ONES = MISC + 256;
constexpr uint32_t CSQ = MISC + 512;
constexpr uint32_t FB = MISC + 1280;
constexpr uint32_t KVS = XS + 2 * 16384 + 12288;
constexpr uint32_t ZS = KVS + 2048;
constexpr uint32_t SMEM_BYTES = 232448;

constexpr int SPIN_LIMIT = 1 << 19;
constexpr uint32_t WAIT_CYCLES = 1u << 28;

__device__ uint4 g_msg[16 * 8 * 8 * 1024];
__device__ float g_kv[2 * 8 * 1088];
__device__ float g_cs[8 * 384];
__device__ unsigned g_flag[8 * 32];
__device__ unsigned g_epoch[128];

__device__ __forceinline__ void mbar_init(uint32_t bar, uint32_t cnt) { asm volatile("mbarrier.init.shared::cta.b64 [%0], %1;" ::"r"(bar), "r"(cnt) : "memory"); }
__device__ __forceinline__ void mbar_expect_tx(uint32_t bar, uint32_t bytes) { asm volatile("mbarrier.arrive.expect_tx.shared::cta.b64 _, [%0], %1;" ::"r"(bar), "r"(bytes) : "memory"); }
__device__ __forceinline__ void mbar_arrive(uint32_t bar) { asm volatile("mbarrier.arrive.shared::cta.b64 _, [%0];" ::"r"(bar) : "memory"); }
__device__ __forceinline__ void mbar_arrive_n(uint32_t bar, uint32_t n) { asm volatile("mbarrier.arrive.shared::cta.b64 _, [%0], %1;" ::"r"(bar), "r"(n) : "memory"); }
__device__ __forceinline__ bool mbar_try(uint32_t bar, uint32_t parity) {
  uint32_t ok;
  asm volatile("{ .reg .pred p; mbarrier.try_wait.parity.shared::cta.b64 p, [%1], %2; selp.u32 %0, 1, 0, p; }" : "=r"(ok) : "r"(bar), "r"(parity) : "memory");
  return ok;
}
__device__ __forceinline__ void mbar_wait(uint32_t bar, uint32_t parity) {
  if (mbar_try(bar, parity)) return;
  const uint32_t t0 = (uint32_t)clock();
  while (!mbar_try(bar, parity)) { if ((uint32_t)clock() - t0 > WAIT_CYCLES) break; }
}
__device__ __forceinline__ void tma2d(uint32_t dst, const CUtensorMap* m, int c0, int c1, uint32_t bar) {
  asm volatile("cp.async.bulk.tensor.2d.shared::cluster.global.mbarrier::complete_tx::bytes [%0], [%1, {%3, %4}], [%2];"
               ::"r"(dst), "l"(m), "r"(bar), "r"(c0), "r"(c1) : "memory");
}
__device__ __forceinline__ void tma3d(uint32_t dst, const CUtensorMap* m, int c0, int c1, int c2, uint32_t bar) {
  asm volatile("cp.async.bulk.tensor.3d.shared::cluster.global.mbarrier::complete_tx::bytes [%0], [%1, {%3, %4, %5}], [%2];"
               ::"r"(dst), "l"(m), "r"(bar), "r"(c0), "r"(c1), "r"(c2) : "memory");
}
__device__ __forceinline__ void prefetch_map(const CUtensorMap* m) { asm volatile("prefetch.tensormap [%0];" ::"l"(m) : "memory"); }
__device__ __forceinline__ void prefetch_l2(const void* p, uint32_t bytes) { asm volatile("cp.async.bulk.prefetch.L2.global [%0], %1;" ::"l"(p), "r"(bytes) : "memory"); }
__device__ __forceinline__ void wg_fence() { asm volatile("wgmma.fence.sync.aligned;" ::: "memory"); }
__device__ __forceinline__ void wg_commit() { asm volatile("wgmma.commit_group.sync.aligned;" ::: "memory"); }
template <int N> __device__ __forceinline__ void wg_wait() { asm volatile("wgmma.wait_group.sync.aligned %0;" ::"n"(N) : "memory"); }
template <int O, int N, int SZ> __device__ __forceinline__ void reg_fence(float (&d)[SZ]) {
#pragma unroll
  for (int k = 0; k < N; k++) asm volatile("" : "+f"(d[O + k])::"memory");
}
__device__ __forceinline__ void fence_async() { asm volatile("fence.proxy.async.shared::cta;" ::: "memory"); }
__device__ __forceinline__ void bar_wg(int id) { asm volatile("bar.sync %0, 128;" ::"r"(id) : "memory"); }
__device__ __forceinline__ uint32_t pack(float lo, float hi) { uint32_t r; asm("cvt.rn.bf16x2.f32 %0, %1, %2;" : "=r"(r) : "f"(hi), "f"(lo)); return r; }
__device__ __forceinline__ float bflo(uint32_t w) { return __uint_as_float(w << 16); }
__device__ __forceinline__ float bfhi(uint32_t w) { return __uint_as_float(w & 0xffff0000u); }
__device__ __forceinline__ float ex2(float x) { float r; asm("ex2.approx.ftz.f32 %0, %1;" : "=f"(r) : "f"(x)); return r; }
__device__ __forceinline__ float rcp(float x) { float r; asm("rcp.approx.ftz.f32 %0, %1;" : "=f"(r) : "f"(x)); return r; }
__device__ __forceinline__ uint4 lds128(uint32_t a) { uint4 v; asm volatile("ld.shared.v4.u32 {%0,%1,%2,%3}, [%4];" : "=r"(v.x), "=r"(v.y), "=r"(v.z), "=r"(v.w) : "r"(a) : "memory"); return v; }
__device__ __forceinline__ float4 lds128f(uint32_t a) { float4 v; asm volatile("ld.shared.v4.f32 {%0,%1,%2,%3}, [%4];" : "=f"(v.x), "=f"(v.y), "=f"(v.z), "=f"(v.w) : "r"(a) : "memory"); return v; }
__device__ __forceinline__ float2 lds64f(uint32_t a) { float2 v; asm volatile("ld.shared.v2.f32 {%0,%1}, [%2];" : "=f"(v.x), "=f"(v.y) : "r"(a) : "memory"); return v; }
__device__ __forceinline__ uint32_t lds32(uint32_t a) { uint32_t v; asm volatile("ld.shared.u32 %0, [%1];" : "=r"(v) : "r"(a) : "memory"); return v; }
__device__ __forceinline__ void sts128(uint32_t a, uint32_t x, uint32_t y, uint32_t z, uint32_t w) { asm volatile("st.shared.v4.u32 [%0], {%1,%2,%3,%4};" ::"r"(a), "r"(x), "r"(y), "r"(z), "r"(w) : "memory"); }
__device__ __forceinline__ void sts128f(uint32_t a, float x, float y, float z, float w) { asm volatile("st.shared.v4.f32 [%0], {%1,%2,%3,%4};" ::"r"(a), "f"(x), "f"(y), "f"(z), "f"(w) : "memory"); }
__device__ __forceinline__ void sts64(uint32_t a, uint32_t x, uint32_t y) { asm volatile("st.shared.v2.u32 [%0], {%1,%2};" ::"r"(a), "r"(x), "r"(y) : "memory"); }
__device__ __forceinline__ void sts32f(uint32_t a, float x) { asm volatile("st.shared.f32 [%0], %1;" ::"r"(a), "f"(x) : "memory"); }
__device__ __forceinline__ void stsm4(uint32_t a, uint32_t r0, uint32_t r1, uint32_t r2, uint32_t r3) {
  asm volatile("stmatrix.sync.aligned.m8n8.x4.shared.b16 [%0], {%1,%2,%3,%4};" ::"r"(a), "r"(r0), "r"(r1), "r"(r2), "r"(r3) : "memory");
}
__device__ __forceinline__ uint4 ldg_nc128(const void* p) { uint4 v; asm volatile("ld.global.nc.L1::no_allocate.v4.u32 {%0,%1,%2,%3}, [%4];" : "=r"(v.x), "=r"(v.y), "=r"(v.z), "=r"(v.w) : "l"(p)); return v; }
__device__ __forceinline__ uint32_t ldg_nc32(const void* p) { uint32_t v; asm volatile("ld.global.nc.u32 %0, [%1];" : "=r"(v) : "l"(p)); return v; }
__device__ __forceinline__ void ld_msg(const uint4* p, uint32_t& x, uint32_t& y, uint32_t& z, uint32_t& w) {
  asm volatile("{ .reg .b128 r; ld.relaxed.gpu.global.b128 r, [%4]; mov.b128 {%0,%1,%2,%3}, r; }" : "=r"(x), "=r"(y), "=r"(z), "=r"(w) : "l"(p) : "memory");
}
__device__ __forceinline__ void st_msg(uint4* p, uint32_t x, uint32_t y, uint32_t z, uint32_t w) {
  asm volatile("{ .reg .b128 r; mov.b128 r, {%1,%2,%3,%4}; st.relaxed.gpu.global.b128 [%0], r; }" ::"l"(p), "r"(x), "r"(y), "r"(z), "r"(w) : "memory");
}
__device__ __forceinline__ float4 ld_rlx128f(const float* p) { float4 v; asm volatile("ld.relaxed.gpu.global.v4.f32 {%0,%1,%2,%3}, [%4];" : "=f"(v.x), "=f"(v.y), "=f"(v.z), "=f"(v.w) : "l"(p) : "memory"); return v; }
__device__ __forceinline__ void red128f(float* p, float x, float y, float z, float w) { asm volatile("red.relaxed.gpu.global.add.v4.f32 [%0], {%1,%2,%3,%4};" ::"l"(p), "f"(x), "f"(y), "f"(z), "f"(w) : "memory"); }
__device__ __forceinline__ void mma16816(float (&c)[4], uint32_t a0, uint32_t a1, uint32_t a2, uint32_t a3, uint32_t b0, uint32_t b1) {
  asm("mma.sync.aligned.m16n8k16.row.col.f32.bf16.bf16.f32 {%0,%1,%2,%3}, {%4,%5,%6,%7}, {%8,%9}, {%10,%10,%10,%10};"
      : "=f"(c[0]), "=f"(c[1]), "=f"(c[2]), "=f"(c[3]) : "r"(a0), "r"(a1), "r"(a2), "r"(a3), "r"(b0), "r"(b1), "f"(0.f));
}

#define R8(d, o) "+f"(d[(o)]), "+f"(d[(o) + 1]), "+f"(d[(o) + 2]), "+f"(d[(o) + 3]), "+f"(d[(o) + 4]), "+f"(d[(o) + 5]), "+f"(d[(o) + 6]), "+f"(d[(o) + 7])
template <int O, int SC, int SZ>
__device__ __forceinline__ void wg128_ss(float (&d)[SZ], uint32_t alo, uint32_t ahi, uint32_t blo, uint32_t bhi) {
  asm volatile("{ .reg .pred p; .reg .b64 da, db; setp.ne.b32 p, %68, 0; mov.b64 da, {%64, %65}; mov.b64 db, {%66, %67};\n"
    "wgmma.mma_async.sync.aligned.m64n128k16.f32.bf16.bf16 {%0,%1,%2,%3,%4,%5,%6,%7,%8,%9,%10,%11,%12,%13,%14,%15,%16,%17,%18,%19,%20,%21,%22,%23,%24,%25,%26,%27,%28,%29,%30,%31,%32,%33,%34,%35,%36,%37,%38,%39,%40,%41,%42,%43,%44,%45,%46,%47,%48,%49,%50,%51,%52,%53,%54,%55,%56,%57,%58,%59,%60,%61,%62,%63}, da, db, p, 1, 1, 0, 1; }"
    : R8(d, O + 0), R8(d, O + 8), R8(d, O + 16), R8(d, O + 24), R8(d, O + 32), R8(d, O + 40), R8(d, O + 48), R8(d, O + 56) : "r"(alo), "r"(ahi), "r"(blo), "r"(bhi), "n"(SC));
}

template <int O, int SC, int SZ>
__device__ __forceinline__ void wg112_ss(float (&d)[SZ], uint32_t alo, uint32_t ahi, uint32_t blo, uint32_t bhi) {
  asm volatile("{ .reg .pred p; .reg .b64 da, db; setp.ne.b32 p, %60, 0; mov.b64 da, {%56, %57}; mov.b64 db, {%58, %59};\n"
    "wgmma.mma_async.sync.aligned.m64n112k16.f32.bf16.bf16 {%0,%1,%2,%3,%4,%5,%6,%7,%8,%9,%10,%11,%12,%13,%14,%15,%16,%17,%18,%19,%20,%21,%22,%23,%24,%25,%26,%27,%28,%29,%30,%31,%32,%33,%34,%35,%36,%37,%38,%39,%40,%41,%42,%43,%44,%45,%46,%47,%48,%49,%50,%51,%52,%53,%54,%55}, da, db, p, 1, 1, 0, 1; }"
    : R8(d, O + 0), R8(d, O + 8), R8(d, O + 16), R8(d, O + 24), R8(d, O + 32), R8(d, O + 40), R8(d, O + 48) : "r"(alo), "r"(ahi), "r"(blo), "r"(bhi), "n"(SC));
}

template <int O, int SC, int SZ>
__device__ __forceinline__ void wg64_ss_tt(float (&d)[SZ], uint32_t alo, uint32_t ahi, uint32_t blo, uint32_t bhi) {
  asm volatile("{ .reg .pred p; .reg .b64 da, db; setp.ne.b32 p, %36, 0; mov.b64 da, {%32, %33}; mov.b64 db, {%34, %35};\n"
    "wgmma.mma_async.sync.aligned.m64n64k16.f32.bf16.bf16 {%0,%1,%2,%3,%4,%5,%6,%7,%8,%9,%10,%11,%12,%13,%14,%15,%16,%17,%18,%19,%20,%21,%22,%23,%24,%25,%26,%27,%28,%29,%30,%31}, da, db, p, 1, 1, 1, 1; }"
    : R8(d, O + 0), R8(d, O + 8), R8(d, O + 16), R8(d, O + 24) : "r"(alo), "r"(ahi), "r"(blo), "r"(bhi), "n"(SC));
}

template <int O, int SC, int SZ>
__device__ __forceinline__ void wg8_ss_tn(float (&d)[SZ], uint32_t alo, uint32_t ahi, uint32_t blo, uint32_t bhi) {
  asm volatile("{ .reg .pred p; .reg .b64 da, db; setp.ne.b32 p, %8, 0; mov.b64 da, {%4, %5}; mov.b64 db, {%6, %7};\n"
    "wgmma.mma_async.sync.aligned.m64n8k16.f32.bf16.bf16 {%0,%1,%2,%3}, da, db, p, 1, 1, 1, 0; }"
    : "+f"(d[O + 0]), "+f"(d[O + 1]), "+f"(d[O + 2]), "+f"(d[O + 3]) : "r"(alo), "r"(ahi), "r"(blo), "r"(bhi), "n"(SC));
}

template <int O, int SC, int SZ>
__device__ __forceinline__ void wg128_rs(float (&d)[SZ], uint32_t a0, uint32_t a1, uint32_t a2, uint32_t a3, uint32_t blo, uint32_t bhi) {
  asm volatile("{ .reg .pred p; .reg .b64 db; setp.ne.b32 p, %70, 0; mov.b64 db, {%68, %69};\n"
    "wgmma.mma_async.sync.aligned.m64n128k16.f32.bf16.bf16 {%0,%1,%2,%3,%4,%5,%6,%7,%8,%9,%10,%11,%12,%13,%14,%15,%16,%17,%18,%19,%20,%21,%22,%23,%24,%25,%26,%27,%28,%29,%30,%31,%32,%33,%34,%35,%36,%37,%38,%39,%40,%41,%42,%43,%44,%45,%46,%47,%48,%49,%50,%51,%52,%53,%54,%55,%56,%57,%58,%59,%60,%61,%62,%63}, {%64,%65,%66,%67}, db, p, 1, 1, 1; }"
    : R8(d, O + 0), R8(d, O + 8), R8(d, O + 16), R8(d, O + 24), R8(d, O + 32), R8(d, O + 40), R8(d, O + 48), R8(d, O + 56) : "r"(a0), "r"(a1), "r"(a2), "r"(a3), "r"(blo), "r"(bhi), "n"(SC));
}

template <int O, int SC, int SZ>
__device__ __forceinline__ void wg64_rs(float (&d)[SZ], uint32_t a0, uint32_t a1, uint32_t a2, uint32_t a3, uint32_t blo, uint32_t bhi) {
  asm volatile("{ .reg .pred p; .reg .b64 db; setp.ne.b32 p, %38, 0; mov.b64 db, {%36, %37};\n"
    "wgmma.mma_async.sync.aligned.m64n64k16.f32.bf16.bf16 {%0,%1,%2,%3,%4,%5,%6,%7,%8,%9,%10,%11,%12,%13,%14,%15,%16,%17,%18,%19,%20,%21,%22,%23,%24,%25,%26,%27,%28,%29,%30,%31}, {%32,%33,%34,%35}, db, p, 1, 1, 1; }"
    : R8(d, O + 0), R8(d, O + 8), R8(d, O + 16), R8(d, O + 24) : "r"(a0), "r"(a1), "r"(a2), "r"(a3), "r"(blo), "r"(bhi), "n"(SC));
}

template <int V> struct IC { static constexpr int v = V; };
template <int I, int N, class Fn> __device__ __forceinline__ void sfor(Fn&& f) {
  if constexpr (I < N) { f(IC<I>{}); sfor<I + 1, N>(f); }
}
#define LAM(X) [&](auto X) __attribute__((always_inline))

constexpr uint32_t DHI = (1024 >> 4) | (1u << 30);
constexpr uint32_t DHI_NS = (128 >> 4);
__host__ __device__ constexpr uint32_t LBO(uint32_t b) { return (b >> 4) << 16; }
__host__ __device__ constexpr int slot_of(int pos) { return pos % 6; }
__host__ __device__ constexpr int fpar_of(int pos) { return (pos / 6 - ((pos % 6 >= 4 && pos >= 12) ? 1 : 0)) & 1; }
constexpr float LOG2E = 1.4426950408889634f;

struct alignas(64) Maps { CUtensorMap x, kv, q, w1ab, w1c, w2, w2c, wo; };

#define TS(role, k)
#define TSG(role, k)

__device__ __forceinline__ float phi(float t, float rs, float rsl) {
  float e = ex2(t * rsl) + 1e-6f;
  float p = fmaf(t, rs, 1.000001f);
  return t > 0.f ? p : e;
}
__device__ __forceinline__ float mish(float h) {
  float e = ex2(fminf(h * LOG2E, 30.f));
  float n = e * (e + 2.f);
  return (h * n) * rcp(n + 2.f);
}

template <int O, int SZ>
__device__ __forceinline__ void send_msg(const float (&a)[SZ], uint4* p, uint32_t tag) {
#pragma unroll
  for (int q = 0; q < 4; q++) {
    uint32_t w0 = pack(a[O + 8 * q], a[O + 8 * q + 1]);
    st_msg(p + q * 128, (w0 & ~1u) | tag, pack(a[O + 8 * q + 2], a[O + 8 * q + 3]), pack(a[O + 8 * q + 4], a[O + 8 * q + 5]), pack(a[O + 8 * q + 6], a[O + 8 * q + 7]));
  }
}
__device__ __forceinline__ void load_msg(uint32_t (&m)[16], const uint4* p) {
#pragma unroll
  for (int q = 0; q < 4; q++) ld_msg(p + q * 128, m[4 * q], m[4 * q + 1], m[4 * q + 2], m[4 * q + 3]);
}
template <bool FIRST>
__device__ __forceinline__ void take_msg(float (&s)[32], uint32_t (&m)[16], const uint4* p, uint32_t tag) {
  uint32_t bad = ((m[0] ^ tag) | (m[4] ^ tag) | (m[8] ^ tag) | (m[12] ^ tag)) & 1u;
  if (bad) {
    int it = 0;
    do {
      load_msg(m, p);
      bad = ((m[0] ^ tag) | (m[4] ^ tag) | (m[8] ^ tag) | (m[12] ^ tag)) & 1u;
    } while (bad && ++it < SPIN_LIMIT);
  }
#pragma unroll
  for (int k = 0; k < 16; k++) {
    uint32_t w = (k & 3) == 0 ? (m[k] & ~1u) : m[k];
    if (FIRST) { s[2 * k] = bflo(w); s[2 * k + 1] = bfhi(w); }
    else { s[2 * k] += bflo(w); s[2 * k + 1] += bfhi(w); }
  }
}

__global__ void __launch_bounds__(384, 1)
fused_kernel(const __grid_constant__ Maps maps, const __nv_bfloat16* __restrict__ x, const __nv_bfloat16* __restrict__ wqkv,
             const __nv_bfloat16* __restrict__ wo, const __nv_bfloat16* __restrict__ w1, const __nv_bfloat16* __restrict__ b1,
             const __nv_bfloat16* __restrict__ w2, __nv_bfloat16* __restrict__ out) {
  extern __shared__ __align__(1024) uint8_t smem_raw[];
  const uint32_t sb = (uint32_t)__cvta_generic_to_shared(smem_raw);
  const int i = blockIdx.x >> 3, j = blockIdx.x & 7;
  const int warp = __shfl_sync(0xffffffffu, threadIdx.x >> 5, 0);
  const int lane = threadIdx.x & 31;

  TS(threadIdx.x >> 7, 0);
  TSG(threadIdx.x >> 7, 62);
  if (warp == 8) {
    if (lane == 0) {
      prefetch_map(&maps.x);
      prefetch_map(&maps.kv);
#pragma unroll
      for (int s = 0; s < 6; s++) { mbar_init(sb + B_FULL + 8 * s, 1); mbar_init(sb + B_EMPTY + 8 * s, 8); }
#pragma unroll
      for (int s = 0; s < 8; s++) mbar_init(sb + B_XFULL + 8 * s, 1);
      mbar_init(sb + B_KVPART, 8); mbar_init(sb + B_KVRDY, 1); mbar_init(sb + B_CSPART, 8); mbar_init(sb + B_CSRDY, 1); mbar_init(sb + B_X2FREE, 8);
      asm volatile("fence.mbarrier_init.release.cluster;" ::: "memory");
    }
  } else if (warp == 11) {
    if (lane < 16) sts128(sb + ONES + lane * 16, 0x3f803f80u, 0x3f803f80u, 0x3f803f80u, 0x3f803f80u);
    fence_async();
  }
  const unsigned epoch = *(volatile unsigned*)&g_epoch[blockIdx.x];
  TS(threadIdx.x >> 7, 41);
  __syncthreads();
  TS(threadIdx.x >> 7, 42);

  if (warp >= 8) {
    asm volatile("setmaxnreg.dec.sync.aligned.u32 40;");
    if (warp <= 9) {
      if (lane == 0) {
        auto phaseB = [&](int m, uint32_t dst, uint32_t bar) {
          const int p2 = 2 * (((j >> 1) + 1 + (m >> 2)) & 3), part = m & 3;
          mbar_expect_tx(bar, part == 2 ? 12288 : 16384);
          const CUtensorMap* mp = part < 2 ? &maps.w2 : (part == 2 ? &maps.w2c : &maps.wo);
          tma3d(dst, mp, 0, part == 3 ? 64 * j : FS * j + 64 * part, p2, bar);
        };
        if (warp == 8) {
#pragma unroll 1
          for (int c = 0; c < 8; c++) {
            mbar_expect_tx(sb + B_XFULL + 8 * c, 16384);
            tma2d(sb + XS + c * 16384, &maps.x, 64 * c, 128 * i, sb + B_XFULL + 8 * c);
            TS(2, 44 + c);
          }
          prefetch_map(&maps.w1ab); prefetch_map(&maps.q); prefetch_map(&maps.w1c);
        } else {
#pragma unroll 1
          for (int c = 0; c < 6; c++) {
            mbar_expect_tx(sb + B_FULL + 8 * c, 16384);
            tma3d(sb + RING + c * 16384, &maps.kv, 64 * j, 64 * c, 0, sb + B_FULL + 8 * c);
          }
          prefetch_map(&maps.w2); prefetch_map(&maps.w2c); prefetch_map(&maps.wo);
        }
        int s = warp == 8 ? 1 : 0, ph = 0;
#pragma unroll 1
        for (int pos = warp == 8 ? 7 : 6; pos < 34; pos += 2) {
          if (pos != 10 && pos != 11) {
            const uint32_t dst = sb + RING + s * 16384, bar = sb + B_FULL + 8 * s;
            mbar_wait(sb + B_EMPTY + 8 * s, ph);
            if (pos < 8) {
              mbar_expect_tx(bar, 16384);
              tma3d(dst, &maps.kv, 64 * j, 64 * pos, 0, bar);
            } else if (pos < 18) {
              mbar_expect_tx(bar, 16384);
              tma3d(dst, &maps.w1ab, FS * j, 64 * (pos < 10 ? pos - 8 : pos - 10), 0, bar);
            } else if (pos < 26) {
              mbar_expect_tx(bar, 16384);
              tma2d(dst, &maps.q, 64 * j, 64 * (pos - 18), bar);
              tma2d(dst + 8192, &maps.w1c, FS * j + 128, 64 * (pos - 18), bar);
            }
            if (pos >= 24 && pos < 32) phaseB(pos - 24, sb + XS + (pos - 24) * 16384, sb + B_XFULL + 8 * (pos - 24));
            if (pos >= 26) phaseB(pos - 18, dst, bar);
          }
          s += 2;
          if (s >= 6) { s -= 6; ph ^= 1; }
        }
      }
    } else if (warp == 10) {
      const uint32_t tag = (epoch + 1) & 1, par = epoch & 1;
      if (lane < 17) *(float4*)&g_kv[((par ^ 1) * 8 + j) * 1088 + i * 68 + lane * 4] = make_float4(0.f, 0.f, 0.f, 0.f);
      if (i < 12) {
        mbar_wait(sb + B_CSPART, 0);
        float a = 0.f;
#pragma unroll
        for (int k = 0; k < 8; k++) a += __uint_as_float(lds32(sb + CSQ + k * 128 + lane * 4));
        asm volatile("st.relaxed.gpu.global.u32 [%0], %1;" ::"l"(&g_cs[j * 384 + i * 32 + lane]), "r"((__float_as_uint(a) & ~1u) | tag) : "memory");
      }
      mbar_wait(sb + B_KVPART, 0);
      TS(2, 10);
      float* kvp = &g_kv[(par * 8 + j) * 1088];
#pragma unroll 2
      for (int k = 0; k < 8; k++) {
        float4 a = lds128f(sb + RING + 4 * 16384 + k * 512 + lane * 16), b = lds128f(sb + RING + 5 * 16384 + k * 512 + lane * 16);
        red128f(kvp + k * 128 + lane * 4, a.x + b.x, a.y + b.y, a.z + b.z, a.w + b.w);
      }
      if (lane < 16) {
        float4 a = lds128f(sb + RING + 4 * 16384 + 4096 + lane * 16), b = lds128f(sb + RING + 5 * 16384 + 4096 + lane * 16);
        red128f(kvp + 1024 + lane * 4, a.x + b.x, a.y + b.y, a.z + b.z, a.w + b.w);
      }
      __syncwarp();
      if (lane == 0) { mbar_arrive_n(sb + B_EMPTY + 8 * 4, 8); mbar_arrive_n(sb + B_EMPTY + 8 * 5, 8); }
      __threadfence();
      __syncwarp();
      if (lane == 0) {
        asm volatile("red.relaxed.gpu.global.add.u32 [%0], 1;" ::"l"(&g_flag[j * 32]) : "memory");
        const unsigned target = 16u * (epoch + 1);
        int it = 0;
        while (true) {
          unsigned v;
          asm volatile("ld.acquire.gpu.global.u32 %0, [%1];" : "=r"(v) : "l"(&g_flag[j * 32]) : "memory");
          if ((int)(v - target) >= 0) break;
          if (++it > SPIN_LIMIT) break;
        }
      }
      __syncwarp();
      TS(2, 11);
      mbar_wait(sb + B_X2FREE, 0);
#pragma unroll 2
      for (int h = 0; h < 4; h++) {
        float4 a = ld_rlx128f(kvp + h * 256 + lane * 4), b = ld_rlx128f(kvp + h * 256 + 128 + lane * 4);
        sts128(sb + KVS + h * 512 + lane * 16, pack(a.x, a.y), pack(b.x, b.y), pack(a.z, a.w), pack(b.z, b.w));
      }
      if (lane < 16) {
        float4 a = ld_rlx128f(kvp + 1024 + lane * 4);
        sts64(sb + ZS + lane * 8, pack(a.x, a.y), pack(a.z, a.w));
      }
      __syncwarp();
      if (lane == 0) mbar_arrive(sb + B_KVRDY);
      TS(2, 12);
    } else {
      const uint32_t tag = (epoch + 1) & 1;
      uint32_t bw[3];
#pragma unroll
      for (int k = 0; k < 3; k++) {
        const int pr = lane + 32 * k;
        bw[k] = (pr < 88 && FS * j + 2 * pr < F_) ? ldg_nc32(b1 + FS * j + 2 * pr) : 0u;
      }
      if (lane == 0) {
        mbar_wait(sb + B_FULL + 8 * 3, 0);
        const int rows = j == 7 ? 9 : 11;
        prefetch_l2(w2 + (size_t)(FS * j + rows * i) * D_, rows * 1024);
        prefetch_l2(wo + (size_t)(64 * j + 4 * i) * D_, 4096);
      }
      __syncwarp();
      float4 c[3];
      int it = 0;
      while (true) {
        uint32_t bad = 0;
#pragma unroll
        for (int k = 0; k < 3; k++) {
          c[k] = ld_rlx128f(&g_cs[j * 384 + (k * 32 + lane) * 4]);
          bad |= (__float_as_uint(c[k].x) ^ tag) | (__float_as_uint(c[k].y) ^ tag) | (__float_as_uint(c[k].z) ^ tag) | (__float_as_uint(c[k].w) ^ tag);
        }
        if (!__any_sync(0xffffffffu, bad & 1)) break;
        if (++it > SPIN_LIMIT) break;
        __nanosleep(100);
      }
      sts128f(sb + CSQ + lane * 16, c[0].x, c[0].y, c[0].z, c[0].w);
      if (lane < 16) sts128f(sb + CSQ + 512 + lane * 16, c[1].x, c[1].y, c[1].z, c[1].w);
      else {
        sts64(sb + FB + (lane - 16) * 32, __float_as_uint(c[1].x), __float_as_uint(c[1].y));
        sts64(sb + FB + (lane - 16) * 32 + 16, __float_as_uint(c[1].z), __float_as_uint(c[1].w));
      }
      if (lane < 28) {
        sts64(sb + FB + (lane + 16) * 32, __float_as_uint(c[2].x), __float_as_uint(c[2].y));
        sts64(sb + FB + (lane + 16) * 32 + 16, __float_as_uint(c[2].z), __float_as_uint(c[2].w));
      }
#pragma unroll
      for (int k = 0; k < 3; k++) {
        const int pr = lane + 32 * k;
        if (pr < 88) sts64(sb + FB + pr * 16 + 8, bw[k] << 16, bw[k] & 0xffff0000u);
      }
      __syncwarp();
      if (lane == 0) mbar_arrive(sb + B_CSRDY);
      TS(2, 13);
    }
  } else {
    asm volatile("setmaxnreg.inc.sync.aligned.u32 232;");
    TS(threadIdx.x >> 7, 43);
    const int w = warp >> 2, wq = warp & 3, g = lane >> 2, t = lane & 3;
    const uint32_t tag = (epoch + 1) & 1;
    const uint32_t alo = ((sb + XS + w * 8192) >> 4) | LBO(16);
    const uint32_t ringlo = ((sb + RING) >> 4) | LBO(8192);
    auto release = [&](uint32_t bar) __attribute__((always_inline)) { if (lane == 0) mbar_arrive(sb + bar); };

    float acc1[64];
    float p0, p1, sa0 = 0.f, sb0 = 0.f, qa0 = 0.f, qb0 = 0.f, sa1 = 0.f, sb1 = 0.f, qa1 = 0.f, qb1 = 0.f;
    uint4 cw[8];
    const uint32_t xrow = sb + XS + (64 * w + 16 * wq + g) * 128;
    sfor<0, 8>(LAM(C) {
      constexpr int c = C.v;
      mbar_wait(sb + B_XFULL + 8 * c, 0);
      TS(w, 44 + c);
      mbar_wait(sb + B_FULL + 8 * slot_of(c), fpar_of(c));
      TS(w, 1 + c);
      wg_fence();
      sfor<0, 4>(LAM(K) { wg128_ss<0, (c | K.v) != 0>(acc1, alo + c * 1024 + K.v * 2, DHI, ringlo + slot_of(c) * 1024 + K.v * 128, DHI); });
      wg_commit();
      if constexpr (c > 0) { wg_wait<1>(); release(B_EMPTY + 8 * slot_of(c - 1)); }
      if constexpr (c == 0) {
        p0 = bflo(lds32(xrow + (g << 4)));
        p1 = bflo(lds32(xrow + 1024 + (g << 4)));
        const int fc = 32 * (i - 6) + 8 * t;
        const bool ok = i < 6 || (i < 12 && fc < FS && FS * j + fc < F_);
        const __nv_bfloat16* src = i < 6 ? wqkv + (i < 4 ? 512 + (i >> 1) * 512 : 0) + 64 * j + 32 * (i & 1) + 8 * t : w1 + FS * j + fc;
        const int ld = i < 6 ? 3 * D_ : F_;
        src += (size_t)(64 * warp + g) * ld;
#pragma unroll
        for (int m = 0; m < 8; m++) cw[m] = ok ? ldg_nc128(src + (size_t)8 * m * ld) : make_uint4(0, 0, 0, 0);
      }
#pragma unroll
      for (int hh = 0; hh < 2; hh++) {
        const uint32_t a = xrow + c * 16384 + (((4 * (hh ^ (g & 1)) + t) ^ g) << 4);
        const uint4 u = lds128(a), v = lds128(a + 1024);
        const uint32_t uu[4] = {u.x, u.y, u.z, u.w}, vv[4] = {v.x, v.y, v.z, v.w};
#pragma unroll
        for (int k = 0; k < 4; k++) {
          float a0 = bflo(uu[k]) - p0, a1 = bfhi(uu[k]) - p0, b0 = bflo(vv[k]) - p1, b1v = bfhi(vv[k]) - p1;
          sa0 += a0; sb0 += a1; qa0 = fmaf(a0, a0, qa0); qb0 = fmaf(a1, a1, qb0);
          sa1 += b0; sb1 += b1v; qa1 = fmaf(b0, b0, qa1); qb1 = fmaf(b1v, b1v, qb1);
        }
      }
      if constexpr (c == 3) {
        if (i < 12) {
          float cs[8];
#pragma unroll
          for (int k = 0; k < 8; k++) cs[k] = 0.f;
#pragma unroll
          for (int m = 0; m < 8; m++) {
            cs[0] += bflo(cw[m].x); cs[1] += bfhi(cw[m].x); cs[2] += bflo(cw[m].y); cs[3] += bfhi(cw[m].y);
            cs[4] += bflo(cw[m].z); cs[5] += bfhi(cw[m].z); cs[6] += bflo(cw[m].w); cs[7] += bfhi(cw[m].w);
          }
#pragma unroll
          for (int k = 0; k < 8; k++) {
            cs[k] += __shfl_xor_sync(0xffffffffu, cs[k], 4);
            cs[k] += __shfl_xor_sync(0xffffffffu, cs[k], 8);
            cs[k] += __shfl_xor_sync(0xffffffffu, cs[k], 16);
          }
          if (g == 0) {
            sts128f(sb + CSQ + warp * 128 + t * 32, cs[0], cs[1], cs[2], cs[3]);
            sts128f(sb + CSQ + warp * 128 + t * 32 + 16, cs[4], cs[5], cs[6], cs[7]);
          }
          __syncwarp();
          release(B_CSPART);
        }
      }
    });
    float nm0, nm1, rs0, rs1;
    {
      float s0 = sa0 + sb0, q0 = qa0 + qb0, s1 = sa1 + sb1, q1 = qa1 + qb1;
#pragma unroll
      for (int o = 1; o <= 2; o++) {
        s0 += __shfl_xor_sync(0xffffffffu, s0, o); q0 += __shfl_xor_sync(0xffffffffu, q0, o);
        s1 += __shfl_xor_sync(0xffffffffu, s1, o); q1 += __shfl_xor_sync(0xffffffffu, q1, o);
      }
      s0 *= (1.f / D_); s1 *= (1.f / D_);
      nm0 = -(p0 + s0); nm1 = -(p1 + s1);
      rs0 = rsqrtf(fmaxf(fmaf(q0, 1.f / D_, -s0 * s0), 0.f) + 1e-5f);
      rs1 = rsqrtf(fmaxf(fmaf(q1, 1.f / D_, -s1 * s1), 0.f) + 1e-5f);
    }
    const float rl0 = rs0 * LOG2E, rl1 = rs1 * LOG2E;

    float acc2[64], kva[32], za[4];
    const uint32_t stg = sb + RING + (4 + w) * 16384;
    const uint32_t stm = stg + (16 * wq + (lane & 15)) * 128;
    sfor<0, 8>(LAM(C) {
      constexpr int c = C.v, pos = c < 2 ? 8 + c : 10 + c, prev = c == 0 ? 7 : (c - 1 < 2 ? 7 + c : 9 + c);
      mbar_wait(sb + B_FULL + 8 * slot_of(pos), fpar_of(pos));
      TS(w, 9 + c);
      wg_fence();
      if constexpr (c == 2) {
        const uint32_t klo = (stg >> 4) | LBO(8192), vlo = klo + 512;
        sfor<0, 4>(LAM(K) { wg64_ss_tt<0, K.v != 0>(kva, vlo + K.v * 128, DHI, klo + K.v * 128, DHI); });
        sfor<0, 4>(LAM(K) { wg8_ss_tn<0, K.v != 0>(za, klo + K.v * 128, DHI, ((sb + ONES) >> 4) | LBO(128), DHI_NS); });
      }
      sfor<0, 4>(LAM(K) { wg128_ss<0, (c | K.v) != 0>(acc2, alo + c * 1024 + K.v * 2, DHI, ringlo + slot_of(pos) * 1024 + K.v * 128, DHI); });
      wg_commit();
      wg_wait<1>();
      release(B_EMPTY + 8 * slot_of(prev));
      if constexpr (c == 0) {
        reg_fence<0, 64>(acc1);
        mbar_wait(sb + B_CSRDY, 0);
        mbar_wait(sb + B_EMPTY + 8 * (4 + w), 0);
        TS(w, 40);
#pragma unroll
        for (int a = 0; a < 8; a += 2) {
          uint32_t r[4];
#pragma unroll
          for (int b = 0; b < 2; b++) {
            const int n = a + b;
            const float2 cs = lds64f(sb + CSQ + n * 32 + t * 8);
            r[2 * b] = pack(phi(fmaf(nm0, cs.x, acc1[4 * n]), rs0, rl0), phi(fmaf(nm0, cs.y, acc1[4 * n + 1]), rs0, rl0));
            r[2 * b + 1] = pack(phi(fmaf(nm1, cs.x, acc1[4 * n + 2]), rs1, rl1), phi(fmaf(nm1, cs.y, acc1[4 * n + 3]), rs1, rl1));
          }
          stsm4(stm + (((a + (lane >> 4)) ^ (lane & 7)) << 4), r[0], r[1], r[2], r[3]);
        }
      }
      if constexpr (c == 1) {
#pragma unroll
        for (int a = 0; a < 8; a += 2) {
          uint32_t r[4];
#pragma unroll
          for (int b = 0; b < 2; b++) {
            const int n = 8 + a + b;
            const float2 cs = lds64f(sb + CSQ + n * 32 + t * 8);
            r[2 * b] = pack(fmaf(nm0, cs.x, acc1[4 * n]) * rs0, fmaf(nm0, cs.y, acc1[4 * n + 1]) * rs0);
            r[2 * b + 1] = pack(fmaf(nm1, cs.x, acc1[4 * n + 2]) * rs1, fmaf(nm1, cs.y, acc1[4 * n + 3]) * rs1);
          }
          stsm4(stm + 8192 + (((a + (lane >> 4)) ^ (lane & 7)) << 4), r[0], r[1], r[2], r[3]);
        }
        fence_async();
        bar_wg(1 + w);
      }
      if constexpr (c == 3) {
        reg_fence<0, 32>(kva);
        reg_fence<0, 4>(za);
        float v[8];
#pragma unroll
        for (int k = 0; k < 8; k++) v[k] = wq == 0 ? kva[k] : (wq == 1 ? kva[8 + k] : (wq == 2 ? kva[16 + k] : kva[24 + k]));
        bar_wg(1 + w);
        sts128f(stg + wq * 1024 + lane * 16, v[0], v[1], v[2], v[3]);
        sts128f(stg + wq * 1024 + 512 + lane * 16, v[4], v[5], v[6], v[7]);
        if (t == 0) { sts32f(stg + 4096 + (16 * wq + g) * 4, za[0]); sts32f(stg + 4096 + (16 * wq + g + 8) * 4, za[2]); }
        fence_async();
        __syncwarp();
        release(B_KVPART);
      }
    });

    float acc3[56];
    uint32_t fr[60];
    auto mish_blk = [&](float a0, float a1, float a2, float a3, int pr, uint32_t& r0, uint32_t& r1) __attribute__((always_inline)) {
      const float4 cb = lds128f(sb + FB + pr * 16 + t * 16);
      r0 = pack(mish(fmaf(fmaf(nm0, cb.x, a0), rs0, cb.z)), mish(fmaf(fmaf(nm0, cb.y, a1), rs0, cb.w)));
      r1 = pack(mish(fmaf(fmaf(nm1, cb.x, a2), rs1, cb.z)), mish(fmaf(fmaf(nm1, cb.y, a3), rs1, cb.w)));
    };
    sfor<0, 8>(LAM(C) {
      constexpr int c = C.v, pos = 18 + c;
      mbar_wait(sb + B_FULL + 8 * slot_of(pos), fpar_of(pos));
      TS(w, 17 + c);
      wg_fence();
      sfor<0, 4>(LAM(K) { wg112_ss<0, (c | K.v) != 0>(acc3, alo + c * 1024 + K.v * 2, DHI, ringlo + slot_of(pos) * 1024 + K.v * 128, DHI); });
      wg_commit();
      wg_wait<1>();
      release(B_EMPTY + 8 * slot_of(pos - 1));
      if constexpr (c == 3) release(B_X2FREE);
      if constexpr (c == 0) reg_fence<0, 64>(acc2);
      mish_blk(acc2[8 * c], acc2[8 * c + 1], acc2[8 * c + 2], acc2[8 * c + 3], 8 * c, fr[4 * c], fr[4 * c + 1]);
      mish_blk(acc2[8 * c + 4], acc2[8 * c + 5], acc2[8 * c + 6], acc2[8 * c + 7], 8 * c + 4, fr[4 * c + 2], fr[4 * c + 3]);
    });

    const uint32_t xlo = (sb + XS) >> 4, rlo = (sb + RING) >> 4;
    uint4* const msg_out = g_msg + (size_t)(i * 64 + j) * 1024 + w * 512 + (threadIdx.x & 127);
    const uint4* const msg_in = g_msg + (size_t)(i * 64 + j * 8) * 1024 + w * 512 + (threadIdx.x & 127);
    const int jp = j >> 1;
    auto tile_wait = [&](auto M) __attribute__((always_inline)) {
      constexpr int m = M.v;
      if constexpr (m < 8) mbar_wait(sb + B_XFULL + 8 * m, 1);
      else mbar_wait(sb + B_FULL + 8 * slot_of(18 + m), fpar_of(18 + m));
    };
    auto tile_lo = [&](auto M) __attribute__((always_inline)) {
      constexpr int m = M.v;
      constexpr uint32_t l = LBO((m & 3) == 2 ? 6144 : 8192);
      if constexpr (m < 8) return (xlo + m * 1024) | l;
      else return (rlo + slot_of(18 + m) * 1024) | l;
    };
    auto stage128 = [&](auto M, float (&acc)[64]) __attribute__((always_inline)) {
      constexpr int m = M.v, part = m & 3, nk = part == 2 ? 3 : 4, f0 = part == 3 ? 44 : 16 * part;
      tile_wait(M);
      const uint32_t blo = tile_lo(M);
      wg_fence();
      sfor<0, nk>(LAM(K) { constexpr int f = f0 + 4 * K.v; wg128_rs<0, (part | K.v) != 0>(acc, fr[f], fr[f + 1], fr[f + 2], fr[f + 3], blo + K.v * 128, DHI); });
      wg_commit();
    };

    float accS1[64];
    TS(w, 25);
    stage128(IC<0>{}, accS1);
    stage128(IC<1>{}, accS1);
    wg_wait<2>();
    release(B_EMPTY + 8 * slot_of(25));
    reg_fence<0, 56>(acc3);
#pragma unroll
    for (int n = 0; n < 6; n++)
      mish_blk(acc3[32 + 4 * n], acc3[33 + 4 * n], acc3[34 + 4 * n], acc3[35 + 4 * n], 64 + 4 * n, fr[32 + 2 * n], fr[33 + 2 * n]);
    TS(w, 26);
    stage128(IC<2>{}, accS1);
    mbar_wait(sb + B_KVRDY, 0);
    tile_wait(IC<3>{});
    TS(w, 27);
    sfor<0, 4>(LAM(H) {
      constexpr int h = H.v;
      const float2 ca = lds64f(sb + CSQ + 512 + h * 64 + t * 8), cb = lds64f(sb + CSQ + 512 + h * 64 + 32 + t * 8);
      const uint4 kb = lds128(sb + KVS + h * 512 + lane * 16);
      const uint32_t z0 = lds32(sb + ZS + h * 32 + t * 4), z1 = lds32(sb + ZS + h * 32 + 16 + t * 4);
      const uint32_t a0 = pack(phi(fmaf(nm0, ca.x, acc3[8 * h]), rs0, rl0), phi(fmaf(nm0, ca.y, acc3[8 * h + 1]), rs0, rl0));
      const uint32_t a1 = pack(phi(fmaf(nm1, ca.x, acc3[8 * h + 2]), rs1, rl1), phi(fmaf(nm1, ca.y, acc3[8 * h + 3]), rs1, rl1));
      const uint32_t a2 = pack(phi(fmaf(nm0, cb.x, acc3[8 * h + 4]), rs0, rl0), phi(fmaf(nm0, cb.y, acc3[8 * h + 5]), rs0, rl0));
      const uint32_t a3 = pack(phi(fmaf(nm1, cb.x, acc3[8 * h + 6]), rs1, rl1), phi(fmaf(nm1, cb.y, acc3[8 * h + 7]), rs1, rl1));
      float n0[4], n1[4], dn[4];
      mma16816(dn, a0, a1, a2, a3, z0, z1);
      mma16816(n0, a0, a1, a2, a3, kb.x, kb.y);
      mma16816(n1, a0, a1, a2, a3, kb.z, kb.w);
      const float r0 = rcp(dn[0] + 1e-6f), r1 = rcp(dn[2] + 1e-6f);
      constexpr int f = 44 + 4 * h;
      fr[f] = pack(n0[0] * r0, n0[1] * r0); fr[f + 1] = pack(n0[2] * r1, n0[3] * r1);
      fr[f + 2] = pack(n1[0] * r0, n1[1] * r0); fr[f + 3] = pack(n1[2] * r1, n1[3] * r1);
      wg_fence();
      wg128_rs<0, 1>(accS1, fr[f], fr[f + 1], fr[f + 2], fr[f + 3], tile_lo(IC<3>{}) + h * 128, DHI);
      wg_commit();
    });
    TS(w, 28);

    float accS2[64];
    stage128(IC<4>{}, accS2);
    wg_wait<1>();
    reg_fence<0, 64>(accS1);
    TS(w, 29);
    {
      uint4* p = msg_out + (size_t)(2 * ((jp + 1) & 3)) * 8192;
      send_msg<0>(accS1, p, tag);
      send_msg<32>(accS1, p + 8192, tag);
    }
    stage128(IC<5>{}, accS2);
    stage128(IC<6>{}, accS2);
    stage128(IC<7>{}, accS2);

    float accS3[64], sum[32];
    uint32_t ma[16], mb[16];
    stage128(IC<8>{}, accS3);
    wg_wait<1>();
    reg_fence<0, 64>(accS2);
    TS(w, 30);
    {
      uint4* p = msg_out + (size_t)(2 * ((jp + 2) & 3)) * 8192;
      send_msg<0>(accS2, p, tag);
      send_msg<32>(accS2, p + 8192, tag);
    }
    const uint4* in1 = msg_in + 2 * ((jp + 3) & 3) * 1024;
    load_msg(ma, in1);
    load_msg(mb, in1 + 1024);
    stage128(IC<9>{}, accS3);
    wg_wait<1>();
    release(B_EMPTY + 8 * slot_of(26));
    stage128(IC<10>{}, accS3);
    wg_wait<1>();
    release(B_EMPTY + 8 * slot_of(27));
    take_msg<true>(sum, ma, in1, tag);
    stage128(IC<11>{}, accS3);
    take_msg<false>(sum, mb, in1 + 1024, tag);
    TS(w, 31);

    float accT[32], accO[32];
    auto stage64 = [&](auto M, float (&acc)[32], uint32_t blk) __attribute__((always_inline)) {
      constexpr int m = M.v, part = m & 3, nk = part == 2 ? 3 : 4, f0 = part == 3 ? 44 : 16 * part;
      const uint32_t blo = tile_lo(M) + blk * (part == 2 ? 384 : 512);
      wg_fence();
      sfor<0, nk>(LAM(K) { constexpr int f = f0 + 4 * K.v; wg64_rs<0, (part | K.v) != 0>(acc, fr[f], fr[f + 1], fr[f + 2], fr[f + 3], blo + K.v * 128, DHI); });
      wg_commit();
    };
    const uint32_t own = j & 1;
    const uint4* in2 = msg_in + 2 * ((jp + 2) & 3) * 1024;
    load_msg(ma, in2);
    tile_wait(IC<12>{});
    stage64(IC<12>{}, accT, own ^ 1);
    tile_wait(IC<13>{});
    stage64(IC<13>{}, accT, own ^ 1);
    wg_wait<2>();
    reg_fence<0, 64>(accS3);
    TS(w, 32);
    {
      uint4* p = msg_out + (size_t)(2 * ((jp + 3) & 3)) * 8192;
      send_msg<0>(accS3, p, tag);
      send_msg<32>(accS3, p + 8192, tag);
    }
    load_msg(mb, in2 + 1024);
    tile_wait(IC<14>{});
    stage64(IC<14>{}, accT, own ^ 1);
    tile_wait(IC<15>{});
    stage64(IC<15>{}, accT, own ^ 1);
    stage64(IC<12>{}, accO, own);
    take_msg<false>(sum, ma, in2, tag);
    wg_wait<1>();
    reg_fence<0, 32>(accT);
    TS(w, 33);
    send_msg<0>(accT, msg_out + (size_t)(j ^ 1) * 8192, tag);
    stage64(IC<13>{}, accO, own);
    stage64(IC<14>{}, accO, own);
    stage64(IC<15>{}, accO, own);
    const uint4* in3 = msg_in + 2 * ((jp + 1) & 3) * 1024;
    load_msg(ma, in3);
    uint32_t xr[16];
    {
      const __nv_bfloat16* xp = x + (size_t)(128 * i + 64 * w + 16 * wq + g) * D_ + 64 * j + 2 * t;
#pragma unroll
      for (int n = 0; n < 8; n++) { xr[2 * n] = ldg_nc32(xp + 8 * n); xr[2 * n + 1] = ldg_nc32(xp + 8 * D_ + 8 * n); }
    }
    take_msg<false>(sum, mb, in2 + 1024, tag);
    load_msg(mb, in3 + 1024);
    take_msg<false>(sum, ma, in3, tag);
    const uint4* in4 = msg_in + (j ^ 1) * 1024;
    load_msg(ma, in4);
    take_msg<false>(sum, mb, in3 + 1024, tag);
#pragma unroll
    for (int k = 0; k < 16; k++) { sum[2 * k] += bflo(xr[k]); sum[2 * k + 1] += bfhi(xr[k]); }
    TS(w, 34);
    take_msg<false>(sum, ma, in4, tag);
    TS(w, 35);
    wg_wait<0>();
    reg_fence<0, 32>(accO);
    TS(w, 36);
    {
      const uint32_t ob = sb + XS + w * 16384 + wq * 2048;
#pragma unroll
      for (int a = 0; a < 8; a += 2)
        stsm4(ob + (lane & 15) * 128 + (((a + (lane >> 4)) ^ (lane & 7)) << 4),
              pack(sum[4 * a] + accO[4 * a], sum[4 * a + 1] + accO[4 * a + 1]), pack(sum[4 * a + 2] + accO[4 * a + 2], sum[4 * a + 3] + accO[4 * a + 3]),
              pack(sum[4 * a + 4] + accO[4 * a + 4], sum[4 * a + 5] + accO[4 * a + 5]), pack(sum[4 * a + 6] + accO[4 * a + 6], sum[4 * a + 7] + accO[4 * a + 7]));
      __syncwarp();
      __nv_bfloat16* op = out + (size_t)(128 * i + 64 * w + 16 * wq + (lane >> 3)) * D_ + 64 * j + 8 * (lane & 7);
#pragma unroll
      for (int m = 0; m < 4; m++) {
        const int row = (lane >> 3) + 4 * m;
        const uint4 v = lds128(ob + row * 128 + (((lane & 7) ^ (row & 7)) << 4));
        *(uint4*)(op + (size_t)4 * m * D_) = v;
      }
    }
    if (threadIdx.x == 0) g_epoch[blockIdx.x] = epoch + 1;
    TS(w, 37);
    TSG(w, 63);
  }
}

typedef CUresult (*EncodeFn)(CUtensorMap*, CUtensorMapDataType, cuuint32_t, void*, const cuuint64_t*, const cuuint64_t*, const cuuint32_t*,
                             const cuuint32_t*, CUtensorMapInterleave, CUtensorMapSwizzle, CUtensorMapL2promotion, CUtensorMapFloatOOBfill);

bool encode(EncodeFn enc, CUtensorMap* m, const void* p, int rank, cuuint64_t d0, cuuint64_t d1, cuuint64_t d2, cuuint64_t s1, cuuint64_t s2,
            cuuint32_t b0, cuuint32_t b1, cuuint32_t b2) {
  cuuint64_t dims[3] = {d0, d1, d2}, strides[2] = {s1, s2};
  cuuint32_t box[3] = {b0, b1, b2}, es[3] = {1, 1, 1};
  return enc(m, CU_TENSOR_MAP_DATA_TYPE_BFLOAT16, rank, (void*)p, dims, strides, box, es, CU_TENSOR_MAP_INTERLEAVE_NONE, CU_TENSOR_MAP_SWIZZLE_128B,
             CU_TENSOR_MAP_L2_PROMOTION_L2_128B, CU_TENSOR_MAP_FLOAT_OOB_FILL_NONE) == CUDA_SUCCESS;
}

}

extern "C" void kernel_launch(void* const* d_in, const int* in_sizes, int n_in, void* d_out, int out_size) {
  const __nv_bfloat16* x = (const __nv_bfloat16*)d_in[0];
  const __nv_bfloat16* wqkv = (const __nv_bfloat16*)d_in[1];
  const __nv_bfloat16* wo = (const __nv_bfloat16*)d_in[2];
  const __nv_bfloat16* w1 = (const __nv_bfloat16*)d_in[4];
  const __nv_bfloat16* b1 = (const __nv_bfloat16*)d_in[5];
  const __nv_bfloat16* w2 = (const __nv_bfloat16*)d_in[6];
  static EncodeFn enc = nullptr;
  if (!enc) {
    void* fn = nullptr;
    cudaDriverEntryPointQueryResult st;
    if (cudaGetDriverEntryPoint("cuTensorMapEncodeTiled", &fn, cudaEnableDefault, &st) != cudaSuccess || !fn) return;
    enc = (EncodeFn)fn;
    cudaFuncSetAttribute(fused_kernel, cudaFuncAttributeMaxDynamicSharedMemorySize, SMEM_BYTES);
  }
  Maps maps;
  bool ok = true;
  ok &= encode(enc, &maps.x, x, 2, D_, S_, 1, D_ * 2, 0, 64, 128, 1);
  ok &= encode(enc, &maps.kv, wqkv + D_, 3, D_, D_, 2, 3 * D_ * 2, D_ * 2, 64, 64, 2);
  ok &= encode(enc, &maps.q, wqkv, 2, D_, D_, 1, 3 * D_ * 2, 0, 64, 64, 1);
  ok &= encode(enc, &maps.w1ab, w1, 3, F_ - 64, D_, 2, F_ * 2, 128, 64, 64, 2);
  ok &= encode(enc, &maps.w1c, w1, 2, F_, D_, 1, F_ * 2, 0, 64, 64, 1);
  ok &= encode(enc, &maps.w2, w2, 3, 64, F_, 8, D_ * 2, 128, 64, 64, 2);
  ok &= encode(enc, &maps.w2c, w2, 3, 64, F_, 8, D_ * 2, 128, 64, 48, 2);
  ok &= encode(enc, &maps.wo, wo, 3, 64, D_, 8, D_ * 2, 128, 64, 64, 2);
  if (!ok) return;
  fused_kernel<<<128, 384, SMEM_BYTES>>>(maps, x, wqkv, wo, w1, b1, w2, (__nv_bfloat16*)d_out);
}
```

```cpp
#include <cuda_runtime.h>
#include <cuda.h>
#include <cuda_bf16.h>
#include <stdint.h>

namespace {

constexpr int S_ = 2048, D_ = 512, F_ = 1376, FS = 176;

constexpr uint32_t SLOT = 16384;
constexpr uint32_t MISC = 14 * SLOT;
constexpr uint32_t B_FULL = MISC, B_EMPTY = MISC + 112;
constexpr uint32_t B_KVPART = MISC + 160, B_CSPART = MISC + 168, B_DONE = MISC + 176;
constexpr uint32_t B_CSPART2 = MISC + 184;
constexpr uint32_t B_PF = MISC + 192;
constexpr uint32_t B_KVRDY = MISC + 224, B_CS2 = MISC + 232;
constexpr uint32_t B_CS1 = MISC + 240, B_OUT = MISC + 248;
constexpr uint32_t B_AF = MISC + 256;
constexpr int NBAR = 40;
constexpr uint32_t ONES = MISC + 320;
constexpr uint32_t CSQ = MISC + 576;
constexpr uint32_t FB = MISC + 1344;
constexpr uint32_t KVS = 13 * SLOT;
constexpr uint32_t SMEM_BYTES = 232448;

constexpr int SPIN_LIMIT = 1 << 19;

__device__ float4 g_kv[2 * 8 * 384];
__device__ float g_cs[8 * 512];
__device__ uint64_t g_st[2048];
__device__ unsigned g_flag[16 * 32];
__device__ unsigned g_epoch[128];

__device__ __forceinline__ void mbar_init(uint32_t bar, uint32_t cnt) { asm volatile("mbarrier.init.shared::cta.b64 [%0], %1;" ::"r"(bar), "r"(cnt) : "memory"); }
__device__ __forceinline__ void mbar_expect_tx(uint32_t bar, uint32_t bytes) { asm volatile("mbarrier.arrive.expect_tx.shared::cta.b64 _, [%0], %1;" ::"r"(bar), "r"(bytes) : "memory"); }
__device__ __forceinline__ void mbar_arrive(uint32_t bar) { asm volatile("mbarrier.arrive.shared::cta.b64 _, [%0];" ::"r"(bar) : "memory"); }
__device__ __forceinline__ void mbar_arrive_n(uint32_t bar, uint32_t n) { asm volatile("mbarrier.arrive.shared::cta.b64 _, [%0], %1;" ::"r"(bar), "r"(n) : "memory"); }
__device__ __forceinline__ bool mbar_try(uint32_t bar, uint32_t parity) {
  uint32_t ok;
  asm volatile("{ .reg .pred p; mbarrier.try_wait.parity.shared::cta.b64 p, [%1], %2; selp.u32 %0, 1, 0, p; }" : "=r"(ok) : "r"(bar), "r"(parity) : "memory");
  return ok;
}
__device__ __forceinline__ bool mbar_test(uint32_t bar, uint32_t parity) {
  uint32_t ok;
  asm volatile("{ .reg .pred p; mbarrier.test_wait.parity.shared::cta.b64 p, [%1], %2; selp.u32 %0, 1, 0, p; }" : "=r"(ok) : "r"(bar), "r"(parity) : "memory");
  return ok;
}
__device__ __forceinline__ void mbar_wait(uint32_t bar, uint32_t parity, uint32_t& left) {
  asm volatile("{ .reg .pred p;\n"
               "W: mbarrier.try_wait.parity.shared::cta.b64 p, [%1], %2;\n"
               "@!p sub.u32 %0, %0, 1;\n"
               "setp.gt.and.s32 p, %0, 0, !p;\n"
               "@p bra W; }" : "+r"(left) : "r"(bar), "r"(parity) : "memory");
}
__device__ __forceinline__ void tma2d(uint32_t dst, const CUtensorMap* m, int c0, int c1, uint32_t bar) {
  asm volatile("cp.async.bulk.tensor.2d.shared::cluster.global.mbarrier::complete_tx::bytes [%0], [%1, {%3, %4}], [%2];"
               ::"r"(dst), "l"(m), "r"(bar), "r"(c0), "r"(c1) : "memory");
}
__device__ __forceinline__ void tma3d(uint32_t dst, const CUtensorMap* m, int c0, int c1, int c2, uint32_t bar) {
  asm volatile("cp.async.bulk.tensor.3d.shared::cluster.global.mbarrier::complete_tx::bytes [%0], [%1, {%3, %4, %5}], [%2];"
               ::"r"(dst), "l"(m), "r"(bar), "r"(c0), "r"(c1), "r"(c2) : "memory");
}
__device__ __forceinline__ void tma2d_store(const CUtensorMap* m, int c0, int c1, uint32_t src) {
  asm volatile("cp.async.bulk.tensor.2d.global.shared::cta.tile.bulk_group [%0, {%1, %2}], [%3];" ::"l"(m), "r"(c0), "r"(c1), "r"(src) : "memory");
}
__device__ __forceinline__ void tma3d_add(const CUtensorMap* m, int c0, int c1, int c2, uint32_t src) {
  asm volatile("cp.reduce.async.bulk.tensor.3d.global.shared::cta.add.tile.bulk_group [%0, {%1, %2, %3}], [%4];" ::"l"(m), "r"(c0), "r"(c1), "r"(c2), "r"(src) : "memory");
}
__device__ __forceinline__ void bulk_commit() { asm volatile("cp.async.bulk.commit_group;" ::: "memory"); }
__device__ __forceinline__ void bulk_wait_read() { asm volatile("cp.async.bulk.wait_group.read 0;" ::: "memory"); }
__device__ __forceinline__ void bulk_wait() { asm volatile("cp.async.bulk.wait_group 0;" ::: "memory"); }
__device__ __forceinline__ void bulk_peer(uint32_t dst, uint32_t src, uint32_t bytes, uint32_t bar) {
  asm volatile("cp.async.bulk.shared::cluster.shared::cta.mbarrier::complete_tx::bytes [%0], [%1], %2, [%3];" ::"r"(dst), "r"(src), "r"(bytes), "r"(bar) : "memory");
}
__device__ __forceinline__ void mbar_arrive_peer(uint32_t bar) { asm volatile("mbarrier.arrive.shared::cluster.b64 _, [%0];" ::"r"(bar) : "memory"); }
__device__ __forceinline__ uint32_t mapa(uint32_t a, uint32_t cta) { uint32_t r; asm("mapa.shared::cluster.u32 %0, %1, %2;" : "=r"(r) : "r"(a), "r"(cta)); return r; }
__device__ __forceinline__ void prefetch_map(const CUtensorMap* m) { asm volatile("prefetch.tensormap [%0];" ::"l"(m) : "memory"); }
__device__ __forceinline__ void prefetch_l2(const void* p, uint32_t bytes) { asm volatile("cp.async.bulk.prefetch.L2.global [%0], %1;" ::"l"(p), "r"(bytes) : "memory"); }
__device__ __forceinline__ void wg_fence() { asm volatile("wgmma.fence.sync.aligned;" ::: "memory"); }
__device__ __forceinline__ void wg_commit() { asm volatile("wgmma.commit_group.sync.aligned;" ::: "memory"); }
template <int N> __device__ __forceinline__ void wg_wait() { asm volatile("wgmma.wait_group.sync.aligned %0;" ::"n"(N) : "memory"); }
template <int O, int N, int SZ> __device__ __forceinline__ void reg_fence(float (&d)[SZ]) {
#pragma unroll
  for (int k = 0; k < N; k++) asm volatile("" : "+f"(d[O + k])::"memory");
}
__device__ __forceinline__ void fence_async() { asm volatile("fence.proxy.async.shared::cta;" ::: "memory"); }
__device__ __forceinline__ void fence_async_all() { asm volatile("fence.proxy.async;" ::: "memory"); }
__device__ __forceinline__ void bar_wg(int id) { asm volatile("bar.sync %0, 128;" ::"r"(id) : "memory"); }
__device__ __forceinline__ uint32_t pack(float lo, float hi) { uint32_t r; asm("cvt.rn.bf16x2.f32 %0, %1, %2;" : "=r"(r) : "f"(hi), "f"(lo)); return r; }
__device__ __forceinline__ float bflo(uint32_t w) { return __uint_as_float(w << 16); }
__device__ __forceinline__ float bfhi(uint32_t w) { return __uint_as_float(w & 0xffff0000u); }
__device__ __forceinline__ float ex2(float x) { float r; asm("ex2.approx.ftz.f32 %0, %1;" : "=f"(r) : "f"(x)); return r; }
__device__ __forceinline__ float rcp(float x) { float r; asm("rcp.approx.ftz.f32 %0, %1;" : "=f"(r) : "f"(x)); return r; }
__device__ __forceinline__ uint4 lds128(uint32_t a) { uint4 v; asm volatile("ld.shared.v4.u32 {%0,%1,%2,%3}, [%4];" : "=r"(v.x), "=r"(v.y), "=r"(v.z), "=r"(v.w) : "r"(a) : "memory"); return v; }
__device__ __forceinline__ float4 lds128f(uint32_t a) { float4 v; asm volatile("ld.shared.v4.f32 {%0,%1,%2,%3}, [%4];" : "=f"(v.x), "=f"(v.y), "=f"(v.z), "=f"(v.w) : "r"(a) : "memory"); return v; }
__device__ __forceinline__ float2 lds64f(uint32_t a) { float2 v; asm volatile("ld.shared.v2.f32 {%0,%1}, [%2];" : "=f"(v.x), "=f"(v.y) : "r"(a) : "memory"); return v; }
__device__ __forceinline__ uint32_t lds32(uint32_t a) { uint32_t v; asm volatile("ld.shared.u32 %0, [%1];" : "=r"(v) : "r"(a) : "memory"); return v; }
__device__ __forceinline__ void sts128(uint32_t a, uint32_t x, uint32_t y, uint32_t z, uint32_t w) { asm volatile("st.shared.v4.u32 [%0], {%1,%2,%3,%4};" ::"r"(a), "r"(x), "r"(y), "r"(z), "r"(w) : "memory"); }
__device__ __forceinline__ void sts128f(uint32_t a, float x, float y, float z, float w) { asm volatile("st.shared.v4.f32 [%0], {%1,%2,%3,%4};" ::"r"(a), "f"(x), "f"(y), "f"(z), "f"(w) : "memory"); }
__device__ __forceinline__ void sts64(uint32_t a, uint32_t x, uint32_t y) { asm volatile("st.shared.v2.u32 [%0], {%1,%2};" ::"r"(a), "r"(x), "r"(y) : "memory"); }
__device__ __forceinline__ void sts32f(uint32_t a, float x) { asm volatile("st.shared.f32 [%0], %1;" ::"r"(a), "f"(x) : "memory"); }
__device__ __forceinline__ void stsm4(uint32_t a, uint32_t r0, uint32_t r1, uint32_t r2, uint32_t r3) {
  asm volatile("stmatrix.sync.aligned.m8n8.x4.shared.b16 [%0], {%1,%2,%3,%4};" ::"r"(a), "r"(r0), "r"(r1), "r"(r2), "r"(r3) : "memory");
}
__device__ __forceinline__ uint4 ldg_nc128(const void* p) { uint4 v; asm volatile("ld.global.nc.L1::no_allocate.v4.u32 {%0,%1,%2,%3}, [%4];" : "=r"(v.x), "=r"(v.y), "=r"(v.z), "=r"(v.w) : "l"(p)); return v; }
__device__ __forceinline__ uint32_t ldg_nc32(const void* p) { uint32_t v; asm volatile("ld.global.nc.u32 %0, [%1];" : "=r"(v) : "l"(p)); return v; }
__device__ __forceinline__ float4 ld_rlx128f(const void* p) { float4 v; asm volatile("ld.relaxed.gpu.global.v4.f32 {%0,%1,%2,%3}, [%4];" : "=f"(v.x), "=f"(v.y), "=f"(v.z), "=f"(v.w) : "l"(p) : "memory"); return v; }
__device__ __forceinline__ void red128f(float4* p, float x, float y, float z, float w) { asm volatile("red.relaxed.gpu.global.add.v4.f32 [%0], {%1,%2,%3,%4};" ::"l"(p), "f"(x), "f"(y), "f"(z), "f"(w) : "memory"); }
__device__ __forceinline__ uint64_t ld_rlx64(const uint64_t* p) { uint64_t v; asm volatile("ld.relaxed.gpu.global.b64 %0, [%1];" : "=l"(v) : "l"(p) : "memory"); return v; }
__device__ __forceinline__ void st_rlx64(uint64_t* p, uint64_t v) { asm volatile("st.relaxed.gpu.global.b64 [%0], %1;" ::"l"(p), "l"(v) : "memory"); }
__device__ __forceinline__ uint32_t ld_rlx32(const unsigned* p) { uint32_t v; asm volatile("ld.relaxed.gpu.global.u32 %0, [%1];" : "=r"(v) : "l"(p) : "memory"); return v; }
__device__ __forceinline__ void st_rlx32(void* p, uint32_t v) { asm volatile("st.relaxed.gpu.global.u32 [%0], %1;" ::"l"(p), "r"(v) : "memory"); }
__device__ __forceinline__ void sts32(uint32_t a, uint32_t x) { asm volatile("st.shared.u32 [%0], %1;" ::"r"(a), "r"(x) : "memory"); }
__device__ __forceinline__ uint2 ldg_nc64(const void* p) { uint2 v; asm volatile("ld.global.nc.v2.u32 {%0,%1}, [%2];" : "=r"(v.x), "=r"(v.y) : "l"(p)); return v; }
__device__ __forceinline__ float add_sat(float a, float b) { float r; asm("add.sat.f32 %0, %1, %2;" : "=f"(r) : "f"(a), "f"(b)); return r; }
__device__ __forceinline__ float2 ldc64f(uint32_t a) { float2 v; asm("ld.shared.v2.f32 {%0,%1}, [%2];" : "=f"(v.x), "=f"(v.y) : "r"(a)); return v; }
__device__ __forceinline__ float4 ldc128f(uint32_t a) { float4 v; asm("ld.shared.v4.f32 {%0,%1,%2,%3}, [%4];" : "=f"(v.x), "=f"(v.y), "=f"(v.z), "=f"(v.w) : "r"(a)); return v; }
__device__ __forceinline__ void pin(uint32_t& a) { asm volatile("" : "+r"(a)::"memory"); }
__device__ __forceinline__ void pin2(uint32_t zero, uint32_t a, uint32_t b) {
  asm volatile("{ .reg .pred p; setp.ne.u32 p, %0, 0; @p st.shared.v2.u32 [%0], {%1, %2}; }" ::"r"(zero), "r"(a), "r"(b) : "memory");
}
#define R8(d, o) "+f"(d[(o)]), "+f"(d[(o) + 1]), "+f"(d[(o) + 2]), "+f"(d[(o) + 3]), "+f"(d[(o) + 4]), "+f"(d[(o) + 5]), "+f"(d[(o) + 6]), "+f"(d[(o) + 7])
template <int O, int SC, int SZ>
__device__ __forceinline__ void wg128_ss(float (&d)[SZ], uint64_t da, uint64_t db) {
  asm volatile("{ .reg .pred p; setp.ne.b32 p, %66, 0;\n"
    "wgmma.mma_async.sync.aligned.m64n128k16.f32.bf16.bf16 {%0,%1,%2,%3,%4,%5,%6,%7,%8,%9,%10,%11,%12,%13,%14,%15,%16,%17,%18,%19,%20,%21,%22,%23,%24,%25,%26,%27,%28,%29,%30,%31,%32,%33,%34,%35,%36,%37,%38,%39,%40,%41,%42,%43,%44,%45,%46,%47,%48,%49,%50,%51,%52,%53,%54,%55,%56,%57,%58,%59,%60,%61,%62,%63}, %64, %65, p, 1, 1, 0, 1; }"
    : R8(d, O + 0), R8(d, O + 8), R8(d, O + 16), R8(d, O + 24), R8(d, O + 32), R8(d, O + 40), R8(d, O + 48), R8(d, O + 56) : "l"(da), "l"(db), "n"(SC));
}

template <int O, int SZ>
__device__ __forceinline__ void wg128_ss_dyn(float (&d)[SZ], uint64_t da, uint64_t db, uint32_t sc) {
  asm volatile("{ .reg .pred p; setp.ne.b32 p, %66, 0;\n"
    "wgmma.mma_async.sync.aligned.m64n128k16.f32.bf16.bf16 {%0,%1,%2,%3,%4,%5,%6,%7,%8,%9,%10,%11,%12,%13,%14,%15,%16,%17,%18,%19,%20,%21,%22,%23,%24,%25,%26,%27,%28,%29,%30,%31,%32,%33,%34,%35,%36,%37,%38,%39,%40,%41,%42,%43,%44,%45,%46,%47,%48,%49,%50,%51,%52,%53,%54,%55,%56,%57,%58,%59,%60,%61,%62,%63}, %64, %65, p, 1, 1, 0, 1; }"
    : R8(d, O + 0), R8(d, O + 8), R8(d, O + 16), R8(d, O + 24), R8(d, O + 32), R8(d, O + 40), R8(d, O + 48), R8(d, O + 56) : "l"(da), "l"(db), "r"(sc));
}

template <int O, int SC, int SZ>
__device__ __forceinline__ void wg112_ss(float (&d)[SZ], uint64_t da, uint64_t db) {
  asm volatile("{ .reg .pred p; setp.ne.b32 p, %58, 0;\n"
    "wgmma.mma_async.sync.aligned.m64n112k16.f32.bf16.bf16 {%0,%1,%2,%3,%4,%5,%6,%7,%8,%9,%10,%11,%12,%13,%14,%15,%16,%17,%18,%19,%20,%21,%22,%23,%24,%25,%26,%27,%28,%29,%30,%31,%32,%33,%34,%35,%36,%37,%38,%39,%40,%41,%42,%43,%44,%45,%46,%47,%48,%49,%50,%51,%52,%53,%54,%55}, %56, %57, p, 1, 1, 0, 1; }"
    : R8(d, O + 0), R8(d, O + 8), R8(d, O + 16), R8(d, O + 24), R8(d, O + 32), R8(d, O + 40), R8(d, O + 48) : "l"(da), "l"(db), "n"(SC));
}

template <int O, int SC, int SZ>
__device__ __forceinline__ void wg64_ss_tt(float (&d)[SZ], uint64_t da, uint64_t db) {
  asm volatile("{ .reg .pred p; setp.ne.b32 p, %34, 0;\n"
    "wgmma.mma_async.sync.aligned.m64n64k16.f32.bf16.bf16 {%0,%1,%2,%3,%4,%5,%6,%7,%8,%9,%10,%11,%12,%13,%14,%15,%16,%17,%18,%19,%20,%21,%22,%23,%24,%25,%26,%27,%28,%29,%30,%31}, %32, %33, p, 1, 1, 1, 1; }"
    : R8(d, O + 0), R8(d, O + 8), R8(d, O + 16), R8(d, O + 24) : "l"(da), "l"(db), "n"(SC));
}

template <int O, int SC, int SZ>
__device__ __forceinline__ void wg8_ss_tn(float (&d)[SZ], uint64_t da, uint64_t db) {
  asm volatile("{ .reg .pred p; setp.ne.b32 p, %6, 0;\n"
    "wgmma.mma_async.sync.aligned.m64n8k16.f32.bf16.bf16 {%0,%1,%2,%3}, %4, %5, p, 1, 1, 1, 0; }"
    : "+f"(d[O + 0]), "+f"(d[O + 1]), "+f"(d[O + 2]), "+f"(d[O + 3]) : "l"(da), "l"(db), "n"(SC));
}

template <int O, int SC, int SZ>
__device__ __forceinline__ void wg128_rs(float (&d)[SZ], uint32_t a0, uint32_t a1, uint32_t a2, uint32_t a3, uint64_t db) {
  asm volatile("{ .reg .pred p; setp.ne.b32 p, %69, 0;\n"
    "wgmma.mma_async.sync.aligned.m64n128k16.f32.bf16.bf16 {%0,%1,%2,%3,%4,%5,%6,%7,%8,%9,%10,%11,%12,%13,%14,%15,%16,%17,%18,%19,%20,%21,%22,%23,%24,%25,%26,%27,%28,%29,%30,%31,%32,%33,%34,%35,%36,%37,%38,%39,%40,%41,%42,%43,%44,%45,%46,%47,%48,%49,%50,%51,%52,%53,%54,%55,%56,%57,%58,%59,%60,%61,%62,%63}, {%64,%65,%66,%67}, %68, p, 1, 1, 1; }"
    : R8(d, O + 0), R8(d, O + 8), R8(d, O + 16), R8(d, O + 24), R8(d, O + 32), R8(d, O + 40), R8(d, O + 48), R8(d, O + 56) : "r"(a0), "r"(a1), "r"(a2), "r"(a3), "l"(db), "n"(SC));
}

template <int O, int SC, int SZ>
__device__ __forceinline__ void wg64_rs(float (&d)[SZ], uint32_t a0, uint32_t a1, uint32_t a2, uint32_t a3, uint64_t db) {
  asm volatile("{ .reg .pred p; setp.ne.b32 p, %37, 0;\n"
    "wgmma.mma_async.sync.aligned.m64n64k16.f32.bf16.bf16 {%0,%1,%2,%3,%4,%5,%6,%7,%8,%9,%10,%11,%12,%13,%14,%15,%16,%17,%18,%19,%20,%21,%22,%23,%24,%25,%26,%27,%28,%29,%30,%31}, {%32,%33,%34,%35}, %36, p, 1, 1, 1; }"
    : R8(d, O + 0), R8(d, O + 8), R8(d, O + 16), R8(d, O + 24) : "r"(a0), "r"(a1), "r"(a2), "r"(a3), "l"(db), "n"(SC));
}

template <int O, int SC, int SZ>
__device__ __forceinline__ void wg24_rs(float (&d)[SZ], uint32_t a0, uint32_t a1, uint32_t a2, uint32_t a3, uint64_t db) {
  asm volatile("{ .reg .pred p; setp.ne.b32 p, %17, 0;\n"
    "wgmma.mma_async.sync.aligned.m64n24k16.f32.bf16.bf16 {%0,%1,%2,%3,%4,%5,%6,%7,%8,%9,%10,%11}, {%12,%13,%14,%15}, %16, p, 1, 1, 0; }"
    : R8(d, O + 0), "+f"(d[O + 8]), "+f"(d[O + 9]), "+f"(d[O + 10]), "+f"(d[O + 11]) : "r"(a0), "r"(a1), "r"(a2), "r"(a3), "l"(db), "n"(SC));
}

template <int V> struct IC { static constexpr int v = V; };
template <int I, int N, class Fn> __device__ __forceinline__ void sfor(Fn&& f) {
  if constexpr (I < N) { f(IC<I>{}); sfor<I + 1, N>(f); }
}
#define LAM(X) [&](auto X) __attribute__((always_inline))
#define INL __attribute__((always_inline))

__host__ __device__ constexpr uint64_t LBO(uint32_t b) { return (uint64_t)(b >> 4) << 16; }
constexpr uint64_t HI_SW = (uint64_t)((1024 >> 4) | (1u << 30)) << 32;
constexpr uint64_t HI_NS = (uint64_t)(256 >> 4) << 32;
constexpr float LOG2E = 1.4426950408889634f, LN2 = 0.6931471805599453f;
#define P1WIN 3

__host__ __device__ constexpr int slotB(int c) { return (int)((0x10321032u >> (4 * c)) & 7); }
__host__ __device__ constexpr int parB(int c) { return c >> 2; }
__host__ __device__ constexpr int slotC(int c) { return (int)((0x32410324u >> (4 * c)) & 7); }
__host__ __device__ constexpr int parC(int c) { return c >= 5; }
__host__ __device__ constexpr int slotM(int m) { return (int)((0xdc9831dc98badc98ull >> (4 * m)) & 15); }
__host__ __device__ constexpr int parM(int m) { return (0x3f03 >> m) & 1; }
__host__ __device__ constexpr int tileM(int m) { return (0xfa48 >> m) & 1; }
__host__ __device__ constexpr int partM(int m) { return (int)((0x2211320210103330ull >> (4 * m)) & 15); }
__host__ __device__ constexpr int peerM(int m) { return (0xa4dc >> m) & 1; }
__host__ __device__ constexpr int slotA(int part, int peer) { return ((peer ? 0x1753 : 0x2640) >> (4 * part)) & 15; }

struct alignas(64) Params {
  CUtensorMap map[9];
  uint64_t zero;
  uint32_t jobs[2][24];
};

#define TS(role, k)
#define TSG(role, k)

__device__ __forceinline__ float phi(float u, float rs, float rl) {
  return fmaxf(add_sat(ex2(u * rl), 1e-6f), fmaf(u, rs, 1.000001f));
}
__device__ __forceinline__ uint32_t mish2(float a0, float a1) {
  const float e0 = ex2(fminf(a0, 30.f)), e1 = ex2(fminf(a1, 30.f));
  const float d0 = fmaf(e0, fmaf(e0, 0.5f * LOG2E, LOG2E), LOG2E), d1 = fmaf(e1, fmaf(e1, 0.5f * LOG2E, LOG2E), LOG2E);
  const float r = rcp(d0 * d1);
  return pack(a0 * fmaf(-r, d1, LN2), a1 * fmaf(-r, d0, LN2));
}

__device__ __forceinline__ void add8(float (&s)[8], const uint4& v) {
  s[0] += bflo(v.x); s[1] += bfhi(v.x); s[2] += bflo(v.y); s[3] += bfhi(v.y);
  s[4] += bflo(v.z); s[5] += bfhi(v.z); s[6] += bflo(v.w); s[7] += bfhi(v.w);
}
__device__ __forceinline__ void rowsum8(float (&s)[8]) {
#pragma unroll
  for (int o = 2; o < 32; o *= 2)
#pragma unroll
    for (int k = 0; k < 8; k++) s[k] += __shfl_xor_sync(0xffffffffu, s[k], o);
}

__global__ void __cluster_dims__(2, 1, 1) __launch_bounds__(384, 1)
fused_kernel(const __grid_constant__ Params prm, const __nv_bfloat16* __restrict__ x, const __nv_bfloat16* __restrict__ wqkv,
             const __nv_bfloat16* __restrict__ wo, const __nv_bfloat16* __restrict__ w1, const __nv_bfloat16* __restrict__ b1,
             const __nv_bfloat16* __restrict__ w2, __nv_bfloat16* __restrict__ out) {
  extern __shared__ __align__(1024) uint8_t smem_raw[];
  const uint32_t sb = __reduce_max_sync(0xffffffffu, (uint32_t)__cvta_generic_to_shared(smem_raw));
  const int i = blockIdx.x >> 3, j = blockIdx.x & 7;
  const int warp = __reduce_max_sync(0xffffffffu, threadIdx.x >> 5);
  const int lane = threadIdx.x & 31;
  uint32_t left = 1u << 16;

  TS(threadIdx.x >> 7, 0);
  TSG(threadIdx.x >> 7, 62);
  uint4 cw0, cw1, xr[4];
  uint32_t epoch;
  if (warp < 8) {
    const __nv_bfloat16* src = wqkv + (size_t)(256 * (i >> 3) + 32 * warp + (lane >> 1)) * (3 * D_) + D_ + ((i >> 2) & 1) * D_ + 64 * j + 16 * (i & 3) + 8 * (lane & 1);
    cw0 = ldg_nc128(src);
    cw1 = ldg_nc128(src + 16 * 3 * D_);
#pragma unroll
    for (int k = 0; k < 4; k++) xr[k] = ldg_nc128(x + (size_t)(128 * i + 16 * j + 2 * warp + (k >> 1)) * D_ + (k & 1) * 256 + 8 * lane);
    epoch = ld_rlx32(&g_epoch[blockIdx.x]);
  } else if (warp == 8) {
    if (lane == 0) {
#pragma unroll
      for (int c = 0; c < P1WIN; c++) mbar_init(sb + B_FULL + 8 * c, 1);
      asm volatile("fence.mbarrier_init.release.cluster;" ::: "memory");
#pragma unroll
      for (int c = 0; c < P1WIN; c++) {
        mbar_expect_tx(sb + B_FULL + 8 * c, 2 * SLOT);
        tma2d(sb + c * SLOT, &prm.map[5], 64 * c, 128 * i, sb + B_FULL + 8 * c);
        tma3d(sb + (8 + c) * SLOT, &prm.map[6], 64 * j, 64 * c, 0, sb + B_FULL + 8 * c);
      }
      TS(2, 44);
    }
  } else if (warp == 9) {
    if (lane == 0) {
#pragma unroll
      for (int k = P1WIN; k < NBAR; k++) mbar_init(sb + MISC + 8 * k, (k < 14 || k >= 30) ? 1 : (k < 24 ? 8 : (k < 28 ? 4 : 2)));
#pragma unroll
      for (int k = 0; k < 8; k++) mbar_expect_tx(sb + B_AF + 8 * k, 8192);
      asm volatile("fence.mbarrier_init.release.cluster;" ::: "memory");
    }
  } else if (warp == 11) {
    if (lane < 16) sts128(sb + ONES + lane * 16, 0x3f803f80u, 0x3f803f80u, 0x3f803f80u, 0x3f803f80u);
    fence_async();
  }
  TS(threadIdx.x >> 7, 41);
  __syncthreads();
  asm volatile("barrier.cluster.arrive.relaxed.aligned;" ::: "memory");
  TS(threadIdx.x >> 7, 42);

  if (warp >= 8) {
    asm volatile("setmaxnreg.dec.sync.aligned.u32 56;");
    if (warp <= 9) {
      if (lane == 0) {
        if (warp == 8) {
#pragma unroll 1
          for (int c = P1WIN; c < 8; c++) {
            const uint32_t bar = sb + B_FULL + 8 * c;
            mbar_wait(bar - 8 * P1WIN, 0, left);
            mbar_expect_tx(bar, 2 * SLOT);
            tma2d(sb + c * SLOT, &prm.map[5], 64 * c, 128 * i, bar);
            if (c >= 6) mbar_wait(sb + B_EMPTY + 8 * (c - 6), 0, left);
            tma3d(sb + (c >= 6 ? c + 2 : c + 8) * SLOT, &prm.map[6], 64 * j, 64 * c, 0, bar);
            TS(2, 44 + c);
          }
        } else {
#pragma unroll
          for (int k = 0; k < 5; k++) prefetch_map(&prm.map[k]);
          mbar_wait(sb + B_FULL + 8 * (7 - P1WIN), 0, left);
        }
#pragma unroll 1
        for (int n = 0; n < 24; n++) {
          const uint32_t job = prm.jobs[warp - 8][n];
          const uint32_t slot = (job >> 6) & 15, mp = (job >> 12) & 7, c = (job >> 15) & 7;
          const uint32_t bar = sb + B_FULL + 8 * slot;
          const int jj = j ^ (job >> 20);
          const int u = (mp == 0 || mp == 4) ? 64 * jj : FS * jj + 64 * ((job >> 18) & 3);
          if ((job & 31) != 31) mbar_wait(sb + MISC + 8 * (job & 31), (job >> 5) & 1, left);
          if (job & 2048) mbar_expect_tx(bar, mp == 3 ? 12288 : SLOT);
          tma3d(sb + slot * SLOT + (job & 1024) * 8, &prm.map[mp], mp < 2 ? u : 0, mp < 2 ? 64 * c : u, mp < 2 ? 0 : 4 * (j & 1) + 2 * (((j >> 1) ^ c) & 1), bar);
        }
      }
    } else {
      epoch = ld_rlx32(&g_epoch[blockIdx.x]);
      const uint32_t tag = (epoch + 1) & 1, par = epoch & 1;
      float* const cs = &g_cs[j * 512];
      auto fresh = [&](const float4& a) INL { return !(((__float_as_uint(a.x) ^ tag) | (__float_as_uint(a.y) ^ tag) | (__float_as_uint(a.z) ^ tag) | (__float_as_uint(a.w) ^ tag)) & 1); };
      if (warp == 10) {
        if (lane < 24) g_kv[((par ^ 1) * 8 + j) * 384 + i * 24 + lane] = make_float4(0.f, 0.f, 0.f, 0.f);
#pragma unroll 1
        for (int p = 0; p < 2; p++) {
          mbar_wait(sb + (p ? B_CSPART2 : B_CSPART), 0, left);
          if (lane < 16) {
            float a = 0.f;
#pragma unroll
            for (int k = 0; k < 8; k++) a += __uint_as_float(lds32(sb + FB + p * 512 + k * 64 + lane * 4));
            st_rlx32(cs + p * 256 + i * 16 + lane, (__float_as_uint(a) & ~1u) | tag);
          }
          TS(2, 9 + p);
        }
        if (lane == 0) {
          mbar_wait(sb + B_FULL + 8 * 7, 0, left);
          tma2d_store(&prm.map[7], 64 * j, 128 * i, sb + j * SLOT);
          bulk_commit();
          prefetch_map(&prm.map[8]);
          bulk_wait_read();
          mbar_arrive(sb + B_CS2);
          bulk_wait();
          fence_async_all();
          asm volatile("red.release.gpu.global.add.u32 [%0], 1;" ::"l"(&g_flag[i * 32]) : "memory");
        }
        __syncwarp();
        TS(2, 11);
      } else {
        mbar_wait(sb + B_FULL, 0, left);
        if (lane == 0) {
#pragma unroll
          for (int k = 0; k < 4; k++) prefetch_l2(wqkv + (size_t)(4 * blockIdx.x + k) * (3 * D_), 1024);
          prefetch_l2(w1 + (size_t)(4 * blockIdx.x) * F_, 4 * F_ * 2);
        }
        float4 a, b;
        int it = 0;
        while (true) {
          a = ld_rlx128f(cs + lane * 4);
          b = ld_rlx128f(cs + 128 + lane * 4);
          if (__all_sync(0xffffffffu, fresh(a) && fresh(b)) || ++it > SPIN_LIMIT) break;
          __nanosleep(64);
        }
        sts128f(sb + CSQ + lane * 16, a.x + b.x, a.y + b.y, a.z + b.z, a.w + b.w);
        __syncwarp();
        if (lane == 0) {
          mbar_arrive(sb + B_CS1);
          TS(2, 13);
          const int rows = j == 7 ? 9 : 11;
          prefetch_l2(w2 + (size_t)(FS * j + rows * i) * D_, rows * 1024);
          prefetch_l2(wo + (size_t)(64 * j + 4 * i) * D_, 4096);
        }
        const int f0 = FS * j + 4 * (lane - 16), f1 = f0 + 128;
        const uint2 bw0 = lane >= 16 ? ldg_nc64(b1 + f0) : make_uint2(0, 0), bw1 = (lane < 28 && f1 < F_) ? ldg_nc64(b1 + f1) : make_uint2(0, 0);
        mbar_wait(sb + B_CSPART2, 0, left);
        it = 0;
        while (true) {
          a = ld_rlx128f(cs + 256 + lane * 4);
          b = ld_rlx128f(cs + 384 + lane * 4);
          if (__all_sync(0xffffffffu, fresh(a) && (lane >= 28 || fresh(b))) || ++it > SPIN_LIMIT) break;
          __nanosleep(64);
        }
        if (lane < 16) sts128f(sb + CSQ + 512 + lane * 16, a.x, a.y, a.z, a.w);
        else {
          sts128f(sb + FB + (lane - 16) * 32, a.x, a.y, bflo(bw0.x) * LOG2E, bfhi(bw0.x) * LOG2E);
          sts128f(sb + FB + (lane - 16) * 32 + 16, a.z, a.w, bflo(bw0.y) * LOG2E, bfhi(bw0.y) * LOG2E);
        }
        if (lane < 28) {
          sts128f(sb + FB + (lane + 16) * 32, b.x, b.y, bflo(bw1.x) * LOG2E, bfhi(bw1.x) * LOG2E);
          sts128f(sb + FB + (lane + 16) * 32 + 16, b.z, b.w, bflo(bw1.y) * LOG2E, bfhi(bw1.y) * LOG2E);
        }
        __syncwarp();
        if (lane == 0) mbar_arrive(sb + B_CS2);
        TS(2, 15);
      }
      mbar_wait(sb + B_KVPART, 0, left);
      TS(2, 12);
      {
        const float4* kvp = &g_kv[(par * 8 + j) * 384 + (warp - 10) * 192 + lane];
        float4 v[6];
        int it = 0;
        while (true) {
          bool done = true;
#pragma unroll
          for (int k = 0; k < 6; k++) v[k] = ld_rlx128f(kvp + 32 * k);
#pragma unroll
          for (int k = 0; k < 6; k++) done = done && v[k].w == 32.f;
          if (__all_sync(0xffffffffu, done) || ++it > SPIN_LIMIT) break;
        }
#pragma unroll
        for (int h = 0; h < 2; h++) {
          const float4 a = v[3 * h], b = v[3 * h + 1], c = v[3 * h + 2];
          const int zl = 8 * (lane & 3);
          const float z0 = __shfl_sync(0xffffffffu, c.z, zl), z1 = __shfl_sync(0xffffffffu, c.z, zl + 4);
          const float z2 = __shfl_sync(0xffffffffu, c.z, zl + 1), z3 = __shfl_sync(0xffffffffu, c.z, zl + 5);
          const uint32_t d = sb + KVS + (2 * (warp - 10) + h) * 768 + lane * 4;
          sts32(d, pack(a.x, a.y)); sts32(d + 256, pack(a.z, b.x)); sts32(d + 128, pack(b.y, b.z)); sts32(d + 384, pack(c.x, c.y));
          sts32(d + 512, pack(z0, z1)); sts32(d + 640, pack(z2, z3));
        }
        fence_async();
        __syncwarp();
        if (lane == 0) mbar_arrive(sb + B_KVRDY);
        TS(2, 14);
      }
      if (warp == 10 && lane == 0) {
        const unsigned target = 8u * (epoch + 1);
        int it = 0;
        while (true) {
          unsigned v;
          asm volatile("ld.acquire.gpu.global.u32 %0, [%1];" : "=r"(v) : "l"(&g_flag[i * 32]) : "memory");
          if ((int)(v - target) >= 0 || ++it > SPIN_LIMIT) break;
          __nanosleep(128);
        }
        fence_async_all();
        mbar_arrive(sb + B_OUT);
        TS(2, 16);
      }
    }
  } else {
    asm volatile("setmaxnreg.inc.sync.aligned.u32 224;");
    const int w = warp >> 2, wq = warp & 3, g = lane >> 2, t = lane & 3;
    uint64_t dB = (uint64_t)((sb & 0x3ffffu) >> 4) | HI_SW | LBO(8192);
    uint64_t dA = dB + (LBO(16) - LBO(8192) + w * 512);
    constexpr uint64_t TO_NS = HI_NS + LBO(128) - HI_SW - LBO(8192);
    auto release = [&](uint32_t bar) INL { if (lane == 0) mbar_arrive(sb + bar); };
    const uint32_t tag = (epoch + 1) & 1;
    auto colsum = [&](float (&s)[8], uint32_t dst, uint32_t bar) INL {
      rowsum8(s);
      if (lane < 2) {
        sts128f(sb + dst + warp * 64 + lane * 32, s[0], s[1], s[2], s[3]);
        sts128f(sb + dst + warp * 64 + lane * 32 + 16, s[4], s[5], s[6], s[7]);
      }
      __syncwarp();
      release(bar);
    };

    float acc1[64];
    bool ok = false;
    sfor<0, 8>(LAM(C) {
      constexpr int c = C.v;
      if (!ok) mbar_wait(sb + B_FULL + 8 * c, 0, left);
      TS(w, 1 + c);
      dA += prm.zero; dB += prm.zero;
      wg_fence();
      sfor<0, 4>(LAM(K) { wg128_ss<0, (c | K.v) != 0>(acc1, dA + c * 1024 + K.v * 2, dB + (c < 6 ? 8 + c : 2 + c) * 1024 + K.v * 128); });
      wg_commit();
      if constexpr (c < 7) ok = mbar_test(sb + B_FULL + 8 * (c + 1), 0);
      else ok = mbar_test(sb + B_FULL + 8 * (8 + slotB(0)), parB(0));
      if constexpr (c == 1) {
        float s[8] = {0.f, 0.f, 0.f, 0.f, 0.f, 0.f, 0.f, 0.f};
        add8(s, cw0); add8(s, cw1);
        colsum(s, FB, B_CSPART);
      }
      if constexpr (c == 2) {
        float v[2][16], m[2], q[2];
#pragma unroll
        for (int r = 0; r < 2; r++) {
          const uint32_t u[8] = {xr[2 * r].x, xr[2 * r].y, xr[2 * r].z, xr[2 * r].w, xr[2 * r + 1].x, xr[2 * r + 1].y, xr[2 * r + 1].z, xr[2 * r + 1].w};
          float a = 0.f, b = 0.f;
#pragma unroll
          for (int k = 0; k < 8; k++) { v[r][2 * k] = bflo(u[k]); v[r][2 * k + 1] = bfhi(u[k]); a += v[r][2 * k]; b += v[r][2 * k + 1]; }
          m[r] = a + b;
        }
#pragma unroll
        for (int o = 1; o < 32; o *= 2) { m[0] += __shfl_xor_sync(0xffffffffu, m[0], o); m[1] += __shfl_xor_sync(0xffffffffu, m[1], o); }
#pragma unroll
        for (int r = 0; r < 2; r++) {
          m[r] *= -1.f / D_;
          float a = 0.f, b = 0.f;
#pragma unroll
          for (int k = 0; k < 8; k++) { const float d0 = v[r][2 * k] + m[r], d1 = v[r][2 * k + 1] + m[r]; a = fmaf(d0, d0, a); b = fmaf(d1, d1, b); }
          q[r] = a + b;
        }
#pragma unroll
        for (int o = 1; o < 32; o *= 2) { q[0] += __shfl_xor_sync(0xffffffffu, q[0], o); q[1] += __shfl_xor_sync(0xffffffffu, q[1], o); }
        const float mm = lane ? m[1] : m[0], rr = rsqrtf(fmaf(lane ? q[1] : q[0], 1.f / D_, 1e-5f));
        if (lane < 2) st_rlx64(&g_st[128 * i + 16 * j + 2 * warp + lane], (uint64_t)__float_as_uint(rr) << 32 | (__float_as_uint(mm) & ~1u) | tag);
        const bool on = i < 4 || (i < 15 && FS * j + 16 * (i - 4) < F_);
        const int ld = i < 4 ? 3 * D_ : F_;
        const __nv_bfloat16* src = (i < 4 ? wqkv + 64 * j + 16 * i : w1 + FS * j + 16 * (i - 4)) + (size_t)(64 * warp + (lane >> 1)) * ld + 8 * (lane & 1);
#pragma unroll
        for (int k = 0; k < 4; k++) xr[k] = on ? ldg_nc128(src + 16 * k * ld) : make_uint4(0, 0, 0, 0);
      }
      if constexpr (c == 5) {
        float s[8] = {0.f, 0.f, 0.f, 0.f, 0.f, 0.f, 0.f, 0.f};
        add8(s, xr[0]); add8(s, xr[1]); add8(s, xr[2]); add8(s, xr[3]);
        colsum(s, FB + 512, B_CSPART2);
      }
      if constexpr (c > 0) { wg_wait<1>(); release(B_EMPTY + 8 * ((c - 1) % 6)); }
    });
    const uint64_t* const stp = &g_st[128 * i + 64 * w + 16 * wq + g];
    uint64_t st0 = ld_rlx64(stp), st1 = ld_rlx64(stp + 8);
    float nm0, nm1, rs0, rs1, rl0, rl1;
    uint32_t cst = sb + CSQ + t * 8, fbt = sb + FB + t * 16;
    const uint32_t zr = (uint32_t)prm.zero;
    auto phi_blk = [&](float a0, float a1, float a2, float a3, int n, uint32_t& r0, uint32_t& r1, bool keep = true) INL {
      const float2 cs = ldc64f(cst + n * 32);
      r0 = pack(phi(fmaf(nm0, cs.x, a0), rs0, rl0), phi(fmaf(nm0, cs.y, a1), rs0, rl0));
      r1 = pack(phi(fmaf(nm1, cs.x, a2), rs1, rl1), phi(fmaf(nm1, cs.y, a3), rs1, rl1));
      if (keep) pin2(zr, r0, r1);
    };
    auto mish_blk = [&](float a0, float a1, float a2, float a3, int n, uint32_t& r0, uint32_t& r1) INL {
      const float4 cb = ldc128f(fbt + n * 64);
      r0 = mish2(fmaf(fmaf(nm0, cb.x, a0), rl0, cb.z), fmaf(fmaf(nm0, cb.y, a1), rl0, cb.w));
      r1 = mish2(fmaf(fmaf(nm1, cb.x, a2), rl1, cb.z), fmaf(fmaf(nm1, cb.y, a3), rl1, cb.w));
    };

    float acc2[64], kva[32], za[4];
    const uint32_t stm = sb + (12 + w) * SLOT + (16 * wq + (lane & 15)) * 128 + (((lane >> 4) ^ (lane & 7)) << 4);
    sfor<0, 8>(LAM(C) {
      constexpr int c = C.v;
      if (!ok) mbar_wait(sb + B_FULL + 8 * (8 + slotB(c)), parB(c), left);
      TS(w, 9 + c);
      dA += prm.zero; dB += prm.zero;
      wg_fence();
      if constexpr (c == 3) {
        const uint64_t dk = dB + 12 * 1024 + w * 1024;
        sfor<0, 4>(LAM(K) { wg64_ss_tt<0, K.v != 0>(kva, dk + 512 + K.v * 128, dk + K.v * 128); });
        sfor<0, 4>(LAM(K) { wg8_ss_tn<0, K.v != 0>(za, dk + K.v * 128, dB + (TO_NS + (ONES >> 4))); });
      }
      sfor<0, 4>(LAM(K) { wg128_ss<0, (c | K.v) != 0>(acc2, dA + c * 1024 + K.v * 2, dB + (8 + slotB(c)) * 1024 + K.v * 128); });
      wg_commit();
      if constexpr (c == 0 || c == 4) { wg_wait<1>(); release(B_EMPTY + 8 * (c == 0 ? 1 : slotB(c == 0 ? 0 : c - 1))); }
      if constexpr (c < 7) ok = mbar_test(sb + B_FULL + 8 * (8 + slotB(c + 1)), parB(c + 1));
      else ok = mbar_test(sb + B_FULL + 8 * (8 + slotC(0)), parC(0));
      if constexpr (c == 0) {
        reg_fence<0, 64>(acc1);
        if (__builtin_expect((((uint32_t)st0 ^ tag) | ((uint32_t)st1 ^ tag)) & 1, 0)) {
          int it = 0;
          do { st0 = ld_rlx64(stp); st1 = ld_rlx64(stp + 8); } while (((((uint32_t)st0 ^ tag) | ((uint32_t)st1 ^ tag)) & 1) && ++it < SPIN_LIMIT);
        }
        nm0 = __uint_as_float((uint32_t)st0); rs0 = __uint_as_float(st0 >> 32); nm1 = __uint_as_float((uint32_t)st1); rs1 = __uint_as_float(st1 >> 32);
        rl0 = rs0 * LOG2E; rl1 = rs1 * LOG2E;
        mbar_wait(sb + B_CS1, 0, left);
        mbar_wait(sb + B_EMPTY + 8 * (4 + w), 0, left);
        pin(cst);
        TS(w, 40);
      }
      if constexpr (c < 2) {
#pragma unroll
        for (int a = 4 * c; a < 4 * c + 4; a += 2) {
          uint32_t r[4];
          phi_blk(acc1[4 * a], acc1[4 * a + 1], acc1[4 * a + 2], acc1[4 * a + 3], a, r[0], r[1], false);
          phi_blk(acc1[4 * a + 4], acc1[4 * a + 5], acc1[4 * a + 6], acc1[4 * a + 7], a + 1, r[2], r[3], false);
          stsm4(stm ^ (a << 4), r[0], r[1], r[2], r[3]);
        }
      }
      if constexpr (c == 2) {
#pragma unroll
        for (int a = 0; a < 8; a += 2) {
          uint32_t r[4];
#pragma unroll
          for (int b = 0; b < 2; b++) {
            const int n = 8 + a + b;
            const float2 cs = ldc64f(cst + n * 32);
            r[2 * b] = pack(fmaf(nm0, cs.x, acc1[4 * n]) * rs0, fmaf(nm0, cs.y, acc1[4 * n + 1]) * rs0);
            r[2 * b + 1] = pack(fmaf(nm1, cs.x, acc1[4 * n + 2]) * rs1, fmaf(nm1, cs.y, acc1[4 * n + 3]) * rs1);
          }
          stsm4((stm ^ (a << 4)) + 8192, r[0], r[1], r[2], r[3]);
        }
        fence_async();
        bar_wg(1 + w);
      }
      if constexpr (c == 4) {
        reg_fence<0, 32>(kva);
        reg_fence<0, 4>(za);
        release(B_KVPART);
        float4* kvp = &g_kv[((epoch & 1) * 8 + j) * 384 + wq * 96 + lane];
        const float z = t == 0 ? za[0] : (t == 1 ? za[2] : 0.f);
        sfor<0, 4>(LAM(H) {
          constexpr int h = H.v;
          if (wq == h) {
            red128f(kvp, kva[8 * h], kva[8 * h + 1], kva[8 * h + 2], 1.f);
            red128f(kvp + 32, kva[8 * h + 3], kva[8 * h + 4], kva[8 * h + 5], 1.f);
            red128f(kvp + 64, kva[8 * h + 6], kva[8 * h + 7], z, 1.f);
          }
        });
      }
      if constexpr (c != 0 && c != 4) { wg_wait<1>(); release(B_EMPTY + 8 * slotB(c == 0 ? 0 : c - 1)); }
    });

    float acc3[56], acco[48];
    uint32_t pq[16];
    const uint32_t sta = stm - 12 * SLOT - w * 8192;
    const uint32_t rows = (64 * w + 16 * wq) * 128;
    const uint32_t peer = __reduce_max_sync(0xffffffffu, mapa(sb, (j & 1) ^ 1));
    auto mish16 = [&](auto O, auto& acc, int n, int part, int a) INL {
      constexpr int o = O.v;
      uint32_t r[4];
      mish_blk(acc[o], acc[o + 1], acc[o + 2], acc[o + 3], n, r[0], r[1]);
      mish_blk(acc[o + 4], acc[o + 5], acc[o + 6], acc[o + 7], n + 1, r[2], r[3]);
      stsm4((sta ^ (a << 4)) + slotA(part, 0) * SLOT, r[0], r[1], r[2], r[3]);
    };
    auto send = [&](int part, int pf) INL {
      fence_async();
      __syncwarp();
      if (lane == 0) {
        if (pf >= 0) mbar_wait(sb + B_PF + pf * 16 + w * 8, 0, left);
        bulk_peer(peer + slotA(part, 1) * SLOT + rows, sb + slotA(part, 0) * SLOT + rows, 2048, peer + B_AF + part * 16 + w * 8);
      }
    };
    asm volatile("barrier.cluster.wait.aligned;" ::: "memory");
    sfor<0, 8>(LAM(C) {
      constexpr int c = C.v;
      if (!ok) mbar_wait(sb + B_FULL + 8 * (8 + slotC(c)), parC(c), left);
      if constexpr (c == 5) { TS(w, 38); mbar_wait(sb + B_KVRDY, 0, left); }
      TS(w, 17 + c);
      dA += prm.zero; dB += prm.zero;
      wg_fence();
      if constexpr (c == 5)
        sfor<0, 4>(LAM(H) { constexpr int h = H.v; wg24_rs<12 * h, 0>(acco, pq[4 * h], pq[4 * h + 1], pq[4 * h + 2], pq[4 * h + 3], dB + (TO_NS + ((KVS + h * 768) >> 4))); });
      sfor<0, 4>(LAM(K) { wg112_ss<0, (c | K.v) != 0>(acc3, dA + c * 1024 + K.v * 2, dB + (8 + slotC(c)) * 1024 + K.v * 128); });
      wg_commit();
      if constexpr (c == 0 || c == 6) { wg_wait<1>(); release(B_EMPTY + 8 * (c == 0 ? slotB(7) : slotC(c == 0 ? 0 : c - 1))); }
      if constexpr (c == 6) release(B_EMPTY + 8 * 5);
      if constexpr (c < 7) ok = mbar_test(sb + B_FULL + 8 * (8 + slotC(c + 1)), parC(c + 1));
      else ok = mbar_test(sb + B_FULL + 8 * slotM(0), parM(0));
      if constexpr (c == 0) { reg_fence<0, 64>(acc2); mbar_wait(sb + B_CS2, 0, left); pin(cst); pin(fbt); TS(w, 39); }
      constexpr int q0 = c < 3 ? 3 * c : 8, q1 = c < 2 ? 3 * c + 3 : 8;
      sfor<q0, q1>(LAM(N) { constexpr int n = N.v; phi_blk(acc2[4 * n], acc2[4 * n + 1], acc2[4 * n + 2], acc2[4 * n + 3], 16 + n, pq[2 * n], pq[2 * n + 1]); });
      if constexpr (c >= 3 && c != 6) { constexpr int a = c == 7 ? 6 : 2 * (c - 3); mish16(IC<32 + 4 * a>{}, acc2, a, 0, a); }
      if constexpr (c == 6) {
        reg_fence<0, 48>(acco);
#pragma unroll
        for (int h = 0; h < 4; h++) {
          const float r0 = rcp(acco[12 * h + 8] + 1e-6f), r1 = rcp(acco[12 * h + 10] + 1e-6f);
          stsm4((sta ^ (h << 5)) + slotA(3, 0) * SLOT, pack(acco[12 * h] * r0, acco[12 * h + 1] * r0), pack(acco[12 * h + 2] * r1, acco[12 * h + 3] * r1),
                pack(acco[12 * h + 4] * r0, acco[12 * h + 5] * r0), pack(acco[12 * h + 6] * r1, acco[12 * h + 7] * r1));
        }
        send(3, 0);
      }
      if constexpr (c == 7) { send(0, -1); bar_wg(1 + w); }
      if constexpr (c != 0 && c != 6) { wg_wait<1>(); release(B_EMPTY + 8 * slotC(c == 0 ? 0 : c - 1)); }
      if constexpr (c == 4) { if (lane == 0) mbar_arrive_peer(peer + B_PF + w * 8); }
    });

    float accX[64], accY[64];
    const uint32_t sto = (lane & 15) * 128 + (((lane >> 4) ^ (lane & 7)) << 4) + wq * 4096;
    auto store_tile = [&](float (&acc)[64], int tile, uint32_t slot) INL {
      const uint32_t st = sb + slot * SLOT + sto;
#pragma unroll
      for (int a = 0; a < 16; a += 2)
        stsm4((st ^ ((a & 7) << 4)) + (a >> 3) * 2048, pack(acc[4 * a], acc[4 * a + 1]), pack(acc[4 * a + 2], acc[4 * a + 3]),
              pack(acc[4 * a + 4], acc[4 * a + 5]), pack(acc[4 * a + 6], acc[4 * a + 7]));
      fence_async();
      __syncwarp();
      if (lane == 0) {
        tma3d_add(&prm.map[8], 0, 128 * i + 64 * w + 16 * wq, 4 * (j & 1) + 2 * (((j >> 1) ^ tile) & 1), sb + slot * SLOT + wq * 4096);
        bulk_commit();
      }
    };
    sfor<0, 16>(LAM(M) {
      constexpr int m = M.v, part = partM(m), nk = part == 2 ? 3 : 4;
      if (!ok) mbar_wait(sb + B_FULL + 8 * slotM(m), parM(m), left);
      if constexpr (m == 2 || m == 4 || m == 7 || m == 10) mbar_wait(sb + B_AF + part * 16 + w * 8, 0, left);
      TS(w, 25 + m < 37 ? 25 + m : 33 + m);
      dA += prm.zero; dB += prm.zero;
      const uint64_t da = dA + slotA(part, peerM(m)) * 1024, db = dB + (LBO(part == 2 ? 6144 : 8192) - LBO(8192) + slotM(m) * 1024);
      wg_fence();
      sfor<0, nk>(LAM(K) {
        if constexpr (tileM(m)) wg128_ss<0, (m != 3 || K.v != 0)>(accY, da + K.v * 2, db + K.v * 128);
        else wg128_ss<0, (m | K.v) != 0>(accX, da + K.v * 2, db + K.v * 128);
      });
      wg_commit();
      if constexpr (m == 0) {
        wg_wait<1>();
        release(B_EMPTY + 8 * slotC(7));
        if (lane == 0) mbar_arrive_peer(peer + B_PF + 16 + w * 8);
        reg_fence<0, 56>(acc3);
      }
      if constexpr (m == 11) { wg_wait<1>(); reg_fence<0, 64>(accX); }
      if constexpr (m < 15) ok = mbar_test(sb + B_FULL + 8 * slotM(m + 1), parM(m + 1));
      if constexpr (m < 7) mish16(IC<8 * m>{}, acc3, 8 + 2 * m, m < 4 ? 1 : 2, 2 * (m & 3));
      if constexpr (m == 3 || m == 6) { send(m == 3 ? 1 : 2, m == 3 ? 1 : -1); bar_wg(1 + w); }
      if constexpr (m == 10) { if (lane == 0) mbar_arrive_peer(peer + B_DONE); }
      if constexpr (m == 11) {
        mbar_wait(sb + B_EMPTY + 8 * (2 + w), 1, left);
        mbar_wait(sb + B_OUT, 0, left);
        store_tile(accX, 0, 10 + w);
        TS(w, 49);
      }
      if constexpr (m != 0 && m != 11 && m != 15) wg_wait<1>();
      if constexpr ((m >= 1 && m <= 10) || m == 13) release(B_EMPTY + 8 * (slotM(m == 0 ? 0 : m - 1) - 8));
    });
    wg_wait<0>();
    reg_fence<0, 64>(accY);
    TS(w, 50);
    mbar_wait(sb + B_EMPTY, 1, left);
    store_tile(accY, 1, 1 + 2 * w);
    TS(w, 51);
    if (lane == 0) {
      bulk_wait_read();
      mbar_wait(sb + B_DONE, 0, left);
    }
    if (threadIdx.x == 0) g_epoch[blockIdx.x] = epoch + 1;
    TS(w, 37);
    TSG(w, 63);
  }
}

typedef CUresult (*EncodeFn)(CUtensorMap*, CUtensorMapDataType, cuuint32_t, void*, const cuuint64_t*, const cuuint64_t*, const cuuint32_t*,
                             const cuuint32_t*, CUtensorMapInterleave, CUtensorMapSwizzle, CUtensorMapL2promotion, CUtensorMapFloatOOBfill);

bool encode(EncodeFn enc, CUtensorMap* m, const void* p, int rank, cuuint64_t d0, cuuint64_t d1, cuuint64_t d2, cuuint64_t s1, cuuint64_t s2,
            cuuint32_t b0, cuuint32_t b1, cuuint32_t b2) {
  cuuint64_t dims[3] = {d0, d1, d2}, strides[2] = {s1, s2};
  cuuint32_t box[3] = {b0, b1, b2}, es[3] = {1, 1, 1};
  return enc(m, CU_TENSOR_MAP_DATA_TYPE_BFLOAT16, rank, (void*)p, dims, strides, box, es, CU_TENSOR_MAP_INTERLEAVE_NONE, CU_TENSOR_MAP_SWIZZLE_128B,
             CU_TENSOR_MAP_L2_PROMOTION_L2_128B, CU_TENSOR_MAP_FLOAT_OOB_FILL_NONE) == CUDA_SUCCESS;
}

constexpr uint32_t job(uint32_t wait_bar, int parity, int slot, int half, int expect, int map, int c, int part, int peer = 0) {
  return (wait_bar ? (wait_bar - MISC) / 8 : 31) | parity << 5 | slot << 6 | half << 10 | expect << 11 | map << 12 | c << 15 | part << 18 | peer << 20;
}
constexpr uint32_t mjob(int ring, int parity, int m) {
  return job(ring < 0 ? 0 : B_EMPTY + 8 * ring, parity, slotM(m), 0, 1, partM(m) < 2 ? 2 : partM(m) + 1, tileM(m), partM(m) == 3 ? 0 : partM(m), peerM(m));
}

}

extern "C" void kernel_launch(void* const* d_in, const int* in_sizes, int n_in, void* d_out, int out_size) {
  const __nv_bfloat16* x = (const __nv_bfloat16*)d_in[0];
  const __nv_bfloat16* wqkv = (const __nv_bfloat16*)d_in[1];
  const __nv_bfloat16* wo = (const __nv_bfloat16*)d_in[2];
  const __nv_bfloat16* w1 = (const __nv_bfloat16*)d_in[4];
  const __nv_bfloat16* b1 = (const __nv_bfloat16*)d_in[5];
  const __nv_bfloat16* w2 = (const __nv_bfloat16*)d_in[6];
  static EncodeFn enc = nullptr;
  if (!enc) {
    void* fn = nullptr;
    cudaDriverEntryPointQueryResult st;
    if (cudaGetDriverEntryPoint("cuTensorMapEncodeTiled", &fn, cudaEnableDefault, &st) != cudaSuccess || !fn) return;
    enc = (EncodeFn)fn;
    cudaFuncSetAttribute(fused_kernel, cudaFuncAttributeMaxDynamicSharedMemorySize, SMEM_BYTES);
  }
  Params prm;
  bool ok = true;
  ok &= encode(enc, &prm.map[0], wqkv, 3, D_, D_, 1, 3 * D_ * 2, 3 * D_ * 2 * D_, 64, 64, 1);
  ok &= encode(enc, &prm.map[1], w1, 3, F_, D_, 1, F_ * 2, F_ * 2 * D_, 64, 64, 1);
  ok &= encode(enc, &prm.map[2], w2, 3, 64, F_, 8, D_ * 2, 128, 64, 64, 2);
  ok &= encode(enc, &prm.map[3], w2, 3, 64, F_, 8, D_ * 2, 128, 64, 48, 2);
  ok &= encode(enc, &prm.map[4], wo, 3, 64, D_, 8, D_ * 2, 128, 64, 64, 2);
  ok &= encode(enc, &prm.map[5], x, 2, D_, S_, 1, D_ * 2, 0, 64, 128, 1);
  ok &= encode(enc, &prm.map[6], wqkv + D_, 3, D_, D_, 2, 3 * D_ * 2, D_ * 2, 64, 64, 2);
  ok &= encode(enc, &prm.map[7], d_out, 2, D_, S_, 1, D_ * 2, 0, 64, 128, 1);
  ok &= encode(enc, &prm.map[8], d_out, 3, 64, S_, 8, D_ * 2, 128, 64, 16, 2);
  if (!ok) return;
  prm.zero = 0;
  for (int p = 0; p < 2; p++) {
    uint32_t* jb = prm.jobs[p];
    int n = 0;
    for (int c = 0; c < 8; c++) jb[n++] = job(B_EMPTY + 8 * slotB(c), c >= 2 && c < 6, 8 + slotB(c), p, 1 - p, p, c, 0);
    for (int c = 0; c < 8; c++) jb[n++] = job(c == 0 ? B_KVPART : B_EMPTY + 8 * slotC(c), c >= 3, 8 + slotC(c), p, 1 - p, 1, c, 1 + p);
    const int ms[2][8][3] = {{{0, 0, 0}, {4, 0, 2}, {2, 0, 4}, {0, 1, 6}, {4, 1, 8}, {0, 0, 11}, {-1, 0, 12}, {4, 0, 14}},
                             {{1, 0, 1}, {5, 1, 3}, {3, 0, 5}, {1, 1, 7}, {5, 0, 9}, {-1, 0, 10}, {1, 0, 13}, {5, 1, 15}}};
    for (int e = 0; e < 8; e++) jb[n++] = mjob(ms[p][e][0], ms[p][e][1], ms[p][e][2]);
  }
  fused_kernel<<<128, 384, SMEM_BYTES>>>(prm, x, wqkv, wo, w1, b1, w2, (__nv_bfloat16*)d_out);
}
```

```cpp
#include <cuda_runtime.h>
#include <cuda.h>
#include <cuda_bf16.h>
#include <stdint.h>

namespace {

constexpr int S_ = 2048, D_ = 512, F_ = 1376, FS = 176;

constexpr uint32_t SLOT = 16384;
constexpr uint32_t MISC = 14 * SLOT;
constexpr uint32_t B_FULL = MISC, B_OUT = MISC + 112, B_KVFREE = MISC + 120;
constexpr uint32_t B_AF = MISC + 128;
constexpr uint32_t B_EMPTY = MISC + 192, B_KVPART = MISC + 240, B_DONE = MISC + 248;
constexpr uint32_t B_PF = MISC + 256;
constexpr uint32_t B_KVRDY = MISC + 288, B_CS2 = MISC + 296, B_CS1 = MISC + 304;
constexpr uint32_t ONES = MISC + 320;
constexpr uint32_t EXT = MISC + 640;
constexpr uint32_t KVS = 13 * SLOT;
constexpr uint32_t SMEM_BYTES = 232448;

constexpr int SPIN_LIMIT = 1 << 19;

constexpr int NSUM = 544, SUM_KV = 384, SUM_QF = 432;
__device__ float4 g_sum[2 * 8 * NSUM];
__device__ float4 g_st[16 * 8 * 8];
__device__ unsigned g_flag[16 * 32];
__device__ unsigned g_epoch[128];

__device__ __forceinline__ void mbar_init(uint32_t bar, uint32_t cnt) { asm volatile("mbarrier.init.shared::cta.b64 [%0], %1;" ::"r"(bar), "r"(cnt) : "memory"); }
__device__ __forceinline__ void mbar_expect_tx(uint32_t bar, uint32_t bytes) { asm volatile("mbarrier.arrive.expect_tx.shared::cta.b64 _, [%0], %1;" ::"r"(bar), "r"(bytes) : "memory"); }
__device__ __forceinline__ void mbar_arrive(uint32_t bar) { asm volatile("mbarrier.arrive.shared::cta.b64 _, [%0];" ::"r"(bar) : "memory"); }
__device__ __forceinline__ void mbar_arrive_n(uint32_t bar, uint32_t n) { asm volatile("mbarrier.arrive.shared::cta.b64 _, [%0], %1;" ::"r"(bar), "r"(n) : "memory"); }
__device__ __forceinline__ bool mbar_try(uint32_t bar, uint32_t parity) {
  uint32_t ok;
  asm volatile("{ .reg .pred p; mbarrier.try_wait.parity.shared::cta.b64 p, [%1], %2; selp.u32 %0, 1, 0, p; }" : "=r"(ok) : "r"(bar), "r"(parity) : "memory");
  return ok;
}
__device__ __forceinline__ bool mbar_test(uint32_t bar, uint32_t parity) {
  uint32_t ok;
  asm volatile("{ .reg .pred p; mbarrier.test_wait.parity.shared::cta.b64 p, [%1], %2; selp.u32 %0, 1, 0, p; }" : "=r"(ok) : "r"(bar), "r"(parity) : "memory");
  return ok;
}
__device__ __forceinline__ bool mbar_test(uint32_t bar, uint32_t parity, float& a, float& b, uint32_t zero) {
  uint32_t ok;
  asm volatile("{ .reg .pred p; mbarrier.test_wait.parity.shared::cta.b64 p, [%3], %4; selp.u32 %0, 1, 0, p; @p add.f32 %1, %1, %5; @p add.f32 %2, %2, %5; }"
               : "=r"(ok), "+f"(a), "+f"(b) : "r"(bar), "r"(parity), "f"(__uint_as_float(zero)) : "memory");
  return ok;
}
__device__ __forceinline__ bool mbar_test(uint32_t bar, uint32_t parity, uint32_t& a, uint32_t& b, uint32_t zero) {
  uint32_t ok;
  asm volatile("{ .reg .pred p; mbarrier.test_wait.parity.shared::cta.b64 p, [%3], %4; selp.u32 %0, 1, 0, p; @p add.u32 %1, %1, %5; @p add.u32 %2, %2, %5; }"
               : "=r"(ok), "+r"(a), "+r"(b) : "r"(bar), "r"(parity), "r"(zero) : "memory");
  return ok;
}
__device__ __forceinline__ void mbar_wait(uint32_t bar, uint32_t parity, uint32_t& left) {
  asm volatile("{ .reg .pred p;\n"
               "W: mbarrier.try_wait.parity.shared::cta.b64 p, [%1], %2;\n"
               "@!p sub.u32 %0, %0, 1;\n"
               "setp.gt.and.s32 p, %0, 0, !p;\n"
               "@p bra W; }" : "+r"(left) : "r"(bar), "r"(parity) : "memory");
}
__device__ __forceinline__ void tma2d(uint32_t dst, const CUtensorMap* m, int c0, int c1, uint32_t bar) {
  asm volatile("cp.async.bulk.tensor.2d.shared::cluster.global.mbarrier::complete_tx::bytes [%0], [%1, {%3, %4}], [%2];"
               ::"r"(dst), "l"(m), "r"(bar), "r"(c0), "r"(c1) : "memory");
}
__device__ __forceinline__ void tma3d(uint32_t dst, const CUtensorMap* m, int c0, int c1, int c2, uint32_t bar) {
  asm volatile("cp.async.bulk.tensor.3d.shared::cluster.global.mbarrier::complete_tx::bytes [%0], [%1, {%3, %4, %5}], [%2];"
               ::"r"(dst), "l"(m), "r"(bar), "r"(c0), "r"(c1), "r"(c2) : "memory");
}
__device__ __forceinline__ void tma2d_store(const CUtensorMap* m, int c0, int c1, uint32_t src) {
  asm volatile("cp.async.bulk.tensor.2d.global.shared::cta.tile.bulk_group [%0, {%1, %2}], [%3];" ::"l"(m), "r"(c0), "r"(c1), "r"(src) : "memory");
}
__device__ __forceinline__ void tma3d_add(const CUtensorMap* m, int c0, int c1, int c2, uint32_t src) {
  asm volatile("cp.reduce.async.bulk.tensor.3d.global.shared::cta.add.tile.bulk_group [%0, {%1, %2, %3}], [%4];" ::"l"(m), "r"(c0), "r"(c1), "r"(c2), "r"(src) : "memory");
}
__device__ __forceinline__ void p1_load_elect(uint32_t bar, uint32_t dx, const CUtensorMap* mx, int cx, int rx, uint32_t dw, const CUtensorMap* mw, int cw) {
  asm volatile("{ .reg .pred p; elect.sync _|p, 0xffffffff;\n"
               "@p mbarrier.arrive.expect_tx.shared::cta.b64 _, [%0], 32768;\n"
               "@p cp.async.bulk.tensor.2d.shared::cluster.global.mbarrier::complete_tx::bytes [%1], [%2, {%3, %4}], [%0];\n"
               "@p cp.async.bulk.tensor.3d.shared::cluster.global.mbarrier::complete_tx::bytes [%5], [%6, {%7, %3, %8}], [%0]; }"
               ::"r"(bar), "r"(dx), "l"(mx), "r"(cx), "r"(rx), "r"(dw), "l"(mw), "r"(cw), "r"(0) : "memory");
}
__device__ __forceinline__ void p1_load_x(uint32_t live, uint32_t bar, uint32_t dst, const CUtensorMap* m, int c0, int c1) {
  asm volatile("{ .reg .pred p; setp.ne.u32 p, %0, 0;\n"
               "@p mbarrier.arrive.expect_tx.shared::cta.b64 _, [%1], 32768;\n"
               "@p cp.async.bulk.tensor.2d.shared::cluster.global.mbarrier::complete_tx::bytes [%2], [%3, {%4, %5}], [%1]; }"
               ::"r"(live), "r"(bar), "r"(dst), "l"(m), "r"(c0), "r"(c1) : "memory");
}
__device__ __forceinline__ void p1_load_w(uint32_t live, uint32_t bar, uint32_t dst, const CUtensorMap* m, int c0, int c1) {
  asm volatile("{ .reg .pred p; setp.ne.u32 p, %0, 0;\n"
               "@p cp.async.bulk.tensor.3d.shared::cluster.global.mbarrier::complete_tx::bytes [%2], [%3, {%4, %5, %6}], [%1]; }"
               ::"r"(live), "r"(bar), "r"(dst), "l"(m), "r"(c0), "r"(c1), "r"(0) : "memory");
}
__device__ __forceinline__ void tma3d_add_elect(const CUtensorMap* m, int c0, int c1, int c2, uint32_t src) {
  asm volatile("{ .reg .pred p; elect.sync _|p, 0xffffffff;\n"
               "@p cp.reduce.async.bulk.tensor.3d.global.shared::cta.add.tile.bulk_group [%0, {%1, %2, %3}], [%4];\n"
               "@p cp.async.bulk.commit_group; }" ::"l"(m), "r"(c0), "r"(c1), "r"(c2), "r"(src) : "memory");
}
__device__ __forceinline__ void bulk_peer_elect(uint32_t dst, uint32_t src, uint32_t bytes, uint32_t bar) {
  asm volatile("{ .reg .pred p; elect.sync _|p, 0xffffffff;\n"
               "@p cp.async.bulk.shared::cluster.shared::cta.mbarrier::complete_tx::bytes [%0], [%1], %2, [%3]; }" ::"r"(dst), "r"(src), "r"(bytes), "r"(bar) : "memory");
}
__device__ __forceinline__ void bulk_commit() { asm volatile("cp.async.bulk.commit_group;" ::: "memory"); }
__device__ __forceinline__ void bulk_wait_read() { asm volatile("cp.async.bulk.wait_group.read 0;" ::: "memory"); }
__device__ __forceinline__ void bulk_wait() { asm volatile("cp.async.bulk.wait_group 0;" ::: "memory"); }
__device__ __forceinline__ void bulk_peer(uint32_t dst, uint32_t src, uint32_t bytes, uint32_t bar) {
  asm volatile("cp.async.bulk.shared::cluster.shared::cta.mbarrier::complete_tx::bytes [%0], [%1], %2, [%3];" ::"r"(dst), "r"(src), "r"(bytes), "r"(bar) : "memory");
}
__device__ __forceinline__ void mbar_arrive_peer(uint32_t bar) { asm volatile("mbarrier.arrive.shared::cluster.b64 _, [%0];" ::"r"(bar) : "memory"); }
__device__ __forceinline__ uint32_t mapa(uint32_t a, uint32_t cta) { uint32_t r; asm("mapa.shared::cluster.u32 %0, %1, %2;" : "=r"(r) : "r"(a), "r"(cta)); return r; }
__device__ __forceinline__ void prefetch_map(const CUtensorMap* m) { asm volatile("prefetch.tensormap [%0];" ::"l"(m) : "memory"); }
__device__ __forceinline__ void prefetch_l2(const void* p, uint32_t bytes) { asm volatile("cp.async.bulk.prefetch.L2.global [%0], %1;" ::"l"(p), "r"(bytes) : "memory"); }
__device__ __forceinline__ void wg_fence() { asm volatile("wgmma.fence.sync.aligned;" ::: "memory"); }
__device__ __forceinline__ void wg_commit() { asm volatile("wgmma.commit_group.sync.aligned;" ::: "memory"); }
template <int N> __device__ __forceinline__ void wg_wait() { asm volatile("wgmma.wait_group.sync.aligned %0;" ::"n"(N) : "memory"); }
template <int O, int N, int SZ> __device__ __forceinline__ void reg_fence(float (&d)[SZ]) {
#pragma unroll
  for (int k = 0; k < N; k++) asm volatile("" : "+f"(d[O + k])::"memory");
}
__device__ __forceinline__ void fence_async() { asm volatile("fence.proxy.async.shared::cta;" ::: "memory"); }
__device__ __forceinline__ void fence_async_all() { asm volatile("fence.proxy.async;" ::: "memory"); }
__device__ __forceinline__ void bar_wg(int id) { asm volatile("bar.sync %0, 128;" ::"r"(id) : "memory"); }
__device__ __forceinline__ uint32_t pack(float lo, float hi) { uint32_t r; asm("cvt.rn.bf16x2.f32 %0, %1, %2;" : "=r"(r) : "f"(hi), "f"(lo)); return r; }
__device__ __forceinline__ float bflo(uint32_t w) { return __uint_as_float(w << 16); }
__device__ __forceinline__ float bfhi(uint32_t w) { return __uint_as_float(w & 0xffff0000u); }
__device__ __forceinline__ float ex2(float x) { float r; asm("ex2.approx.ftz.f32 %0, %1;" : "=f"(r) : "f"(x)); return r; }
__device__ __forceinline__ float sqrt_(float x) { float r; asm("sqrt.approx.ftz.f32 %0, %1;" : "=f"(r) : "f"(x)); return r; }
__device__ __forceinline__ float rcp(float x) { float r; asm("rcp.approx.ftz.f32 %0, %1;" : "=f"(r) : "f"(x)); return r; }
__device__ __forceinline__ uint4 lds128(uint32_t a) { uint4 v; asm volatile("ld.shared.v4.u32 {%0,%1,%2,%3}, [%4];" : "=r"(v.x), "=r"(v.y), "=r"(v.z), "=r"(v.w) : "r"(a) : "memory"); return v; }
__device__ __forceinline__ float4 lds128f(uint32_t a) { float4 v; asm volatile("ld.shared.v4.f32 {%0,%1,%2,%3}, [%4];" : "=f"(v.x), "=f"(v.y), "=f"(v.z), "=f"(v.w) : "r"(a) : "memory"); return v; }
__device__ __forceinline__ float2 lds64f(uint32_t a) { float2 v; asm volatile("ld.shared.v2.f32 {%0,%1}, [%2];" : "=f"(v.x), "=f"(v.y) : "r"(a) : "memory"); return v; }
__device__ __forceinline__ uint32_t lds32(uint32_t a) { uint32_t v; asm volatile("ld.shared.u32 %0, [%1];" : "=r"(v) : "r"(a) : "memory"); return v; }
__device__ __forceinline__ void sts128(uint32_t a, uint32_t x, uint32_t y, uint32_t z, uint32_t w) { asm volatile("st.shared.v4.u32 [%0], {%1,%2,%3,%4};" ::"r"(a), "r"(x), "r"(y), "r"(z), "r"(w) : "memory"); }
__device__ __forceinline__ void sts128f(uint32_t a, float x, float y, float z, float w) { asm volatile("st.shared.v4.f32 [%0], {%1,%2,%3,%4};" ::"r"(a), "f"(x), "f"(y), "f"(z), "f"(w) : "memory"); }
__device__ __forceinline__ void sts64(uint32_t a, uint32_t x, uint32_t y) { asm volatile("st.shared.v2.u32 [%0], {%1,%2};" ::"r"(a), "r"(x), "r"(y) : "memory"); }
__device__ __forceinline__ void sts32f(uint32_t a, float x) { asm volatile("st.shared.f32 [%0], %1;" ::"r"(a), "f"(x) : "memory"); }
__device__ __forceinline__ void stsm4(uint32_t a, uint32_t r0, uint32_t r1, uint32_t r2, uint32_t r3) {
  asm volatile("stmatrix.sync.aligned.m8n8.x4.shared.b16 [%0], {%1,%2,%3,%4};" ::"r"(a), "r"(r0), "r"(r1), "r"(r2), "r"(r3) : "memory");
}
__device__ __forceinline__ void mma16816(float (&d)[4], uint32_t a0, uint32_t a1, uint32_t a2, uint32_t a3, uint32_t b0, uint32_t b1) {
  asm volatile("mma.sync.aligned.m16n8k16.row.col.f32.bf16.bf16.f32 {%0,%1,%2,%3}, {%4,%5,%6,%7}, {%8,%9}, {%0,%1,%2,%3};"
               : "+f"(d[0]), "+f"(d[1]), "+f"(d[2]), "+f"(d[3]) : "r"(a0), "r"(a1), "r"(a2), "r"(a3), "r"(b0), "r"(b1));
}
__device__ __forceinline__ uint32_t sub_bf2(uint32_t a, uint32_t b) { uint32_t r; asm("sub.rn.bf16x2 %0, %1, %2;" : "=r"(r) : "r"(a), "r"(b)); return r; }
__device__ __forceinline__ void ldsm4(uint32_t a, uint32_t* r) {
  asm volatile("ldmatrix.sync.aligned.m8n8.x4.shared.b16 {%0,%1,%2,%3}, [%4];" : "=r"(r[0]), "=r"(r[1]), "=r"(r[2]), "=r"(r[3]) : "r"(a) : "memory");
}
__device__ __forceinline__ uint4 ldg_nc128(const void* p) { uint4 v; asm volatile("ld.global.nc.L1::no_allocate.v4.u32 {%0,%1,%2,%3}, [%4];" : "=r"(v.x), "=r"(v.y), "=r"(v.z), "=r"(v.w) : "l"(p)); return v; }
__device__ __forceinline__ uint32_t ldg_nc32(const void* p) { uint32_t v; asm volatile("ld.global.nc.u32 %0, [%1];" : "=r"(v) : "l"(p)); return v; }
__device__ __forceinline__ float4 ld_rlx128f(const void* p) { float4 v; asm volatile("ld.relaxed.gpu.global.v4.f32 {%0,%1,%2,%3}, [%4];" : "=f"(v.x), "=f"(v.y), "=f"(v.z), "=f"(v.w) : "l"(p) : "memory"); return v; }
__device__ __forceinline__ void red128f(float4* p, float x, float y, float z, float w) { asm volatile("red.relaxed.gpu.global.add.v4.f32 [%0], {%1,%2,%3,%4};" ::"l"(p), "f"(x), "f"(y), "f"(z), "f"(w) : "memory"); }
__device__ __forceinline__ uint64_t ld_rlx64(const uint64_t* p) { uint64_t v; asm volatile("ld.relaxed.gpu.global.b64 %0, [%1];" : "=l"(v) : "l"(p) : "memory"); return v; }
__device__ __forceinline__ void ld_rlx2x64(const uint64_t* p, uint64_t& a, uint64_t& b) { asm volatile("ld.relaxed.gpu.global.v2.b64 {%0,%1}, [%2];" : "=l"(a), "=l"(b) : "l"(p) : "memory"); }
__device__ __forceinline__ void st_rlx128(void* p, uint32_t x, uint32_t y, uint32_t z, uint32_t w) { asm volatile("st.relaxed.gpu.global.v4.u32 [%0], {%1,%2,%3,%4};" ::"l"(p), "r"(x), "r"(y), "r"(z), "r"(w) : "memory"); }
__device__ __forceinline__ void st_rlx64(void* p, uint32_t x, uint32_t y) { asm volatile("st.relaxed.gpu.global.v2.u32 [%0], {%1,%2};" ::"l"(p), "r"(x), "r"(y) : "memory"); }
__device__ __forceinline__ uint2 lds64(uint32_t a) { uint2 v; asm volatile("ld.shared.v2.u32 {%0,%1}, [%2];" : "=r"(v.x), "=r"(v.y) : "r"(a) : "memory"); return v; }
__device__ __forceinline__ void st_rlx64(uint64_t* p, uint64_t v) { asm volatile("st.relaxed.gpu.global.b64 [%0], %1;" ::"l"(p), "l"(v) : "memory"); }
__device__ __forceinline__ uint32_t ld_rlx32(const unsigned* p) { uint32_t v; asm volatile("ld.relaxed.gpu.global.u32 %0, [%1];" : "=r"(v) : "l"(p) : "memory"); return v; }
__device__ __forceinline__ void st_rlx32(void* p, uint32_t v) { asm volatile("st.relaxed.gpu.global.u32 [%0], %1;" ::"l"(p), "r"(v) : "memory"); }
__device__ __forceinline__ void sts32(uint32_t a, uint32_t x) { asm volatile("st.shared.u32 [%0], %1;" ::"r"(a), "r"(x) : "memory"); }
__device__ __forceinline__ void sts16(uint32_t a, uint32_t x) { asm volatile("{ .reg .b16 h; cvt.u16.u32 h, %1; st.shared.u16 [%0], h; }" ::"r"(a), "r"(x) : "memory"); }
__device__ __forceinline__ uint2 ldg_nc64(const void* p) { uint2 v; asm volatile("ld.global.nc.v2.u32 {%0,%1}, [%2];" : "=r"(v.x), "=r"(v.y) : "l"(p)); return v; }
__device__ __forceinline__ float add_sat(float a, float b) { float r; asm("add.sat.f32 %0, %1, %2;" : "=f"(r) : "f"(a), "f"(b)); return r; }
__device__ __forceinline__ float2 ldc64f(uint32_t a) { float2 v; asm("ld.shared.v2.f32 {%0,%1}, [%2];" : "=f"(v.x), "=f"(v.y) : "r"(a)); return v; }
__device__ __forceinline__ float4 ldc128f(uint32_t a) { float4 v; asm("ld.shared.v4.f32 {%0,%1,%2,%3}, [%4];" : "=f"(v.x), "=f"(v.y), "=f"(v.z), "=f"(v.w) : "r"(a)); return v; }
__device__ __forceinline__ void pin(uint32_t& a) { asm volatile("" : "+r"(a)::"memory"); }
__device__ __forceinline__ void pin2(uint32_t zero, uint32_t a, uint32_t b) {
  asm volatile("{ .reg .pred p; setp.ne.u32 p, %0, 0; @p st.shared.v2.u32 [%0], {%1, %2}; }" ::"r"(zero), "r"(a), "r"(b) : "memory");
}
__device__ __forceinline__ void pin4(uint32_t zero, const float (&a)[4]) {
  asm volatile("{ .reg .pred p; setp.ne.u32 p, %0, 0; @p st.shared.v4.f32 [%0], {%1, %2, %3, %4}; }" ::"r"(zero), "f"(a[0]), "f"(a[1]), "f"(a[2]), "f"(a[3]) : "memory");
}
constexpr uint32_t HI_SW = (1024 >> 4) | (1u << 30);
constexpr uint32_t HI_NS = 256 >> 4;
constexpr uint32_t HI_EX = 144 >> 4;
#define R8(d, o) "+f"(d[(o)]), "+f"(d[(o) + 1]), "+f"(d[(o) + 2]), "+f"(d[(o) + 3]), "+f"(d[(o) + 4]), "+f"(d[(o) + 5]), "+f"(d[(o) + 6]), "+f"(d[(o) + 7])
template <int O, int SC, uint32_t HA = HI_SW, uint32_t HB = HI_SW, int SZ>
__device__ __forceinline__ void wg128_ss(float (&d)[SZ], uint32_t da, uint32_t db) {
  asm volatile("{ .reg .pred p; .reg .b32 h, k; .reg .b64 a, b; setp.ne.b32 p, %66, 0; mov.b32 h, %67; mov.b32 k, %68; mov.b64 a, {%64, h}; mov.b64 b, {%65, k};\n"
    "wgmma.mma_async.sync.aligned.m64n128k16.f32.bf16.bf16 {%0,%1,%2,%3,%4,%5,%6,%7,%8,%9,%10,%11,%12,%13,%14,%15,%16,%17,%18,%19,%20,%21,%22,%23,%24,%25,%26,%27,%28,%29,%30,%31,%32,%33,%34,%35,%36,%37,%38,%39,%40,%41,%42,%43,%44,%45,%46,%47,%48,%49,%50,%51,%52,%53,%54,%55,%56,%57,%58,%59,%60,%61,%62,%63}, a, b, p, 1, 1, 0, 1; }"
    : R8(d, O + 0), R8(d, O + 8), R8(d, O + 16), R8(d, O + 24), R8(d, O + 32), R8(d, O + 40), R8(d, O + 48), R8(d, O + 56) : "r"(da), "r"(db), "n"(SC), "n"(HA), "n"(HB));
}

template <int O, int SC, uint32_t HA = HI_SW, uint32_t HB = HI_SW, int SZ>
__device__ __forceinline__ void wg112_ss(float (&d)[SZ], uint32_t da, uint32_t db) {
  asm volatile("{ .reg .pred p; .reg .b32 h, k; .reg .b64 a, b; setp.ne.b32 p, %58, 0; mov.b32 h, %59; mov.b32 k, %60; mov.b64 a, {%56, h}; mov.b64 b, {%57, k};\n"
    "wgmma.mma_async.sync.aligned.m64n112k16.f32.bf16.bf16 {%0,%1,%2,%3,%4,%5,%6,%7,%8,%9,%10,%11,%12,%13,%14,%15,%16,%17,%18,%19,%20,%21,%22,%23,%24,%25,%26,%27,%28,%29,%30,%31,%32,%33,%34,%35,%36,%37,%38,%39,%40,%41,%42,%43,%44,%45,%46,%47,%48,%49,%50,%51,%52,%53,%54,%55}, a, b, p, 1, 1, 0, 1; }"
    : R8(d, O + 0), R8(d, O + 8), R8(d, O + 16), R8(d, O + 24), R8(d, O + 32), R8(d, O + 40), R8(d, O + 48) : "r"(da), "r"(db), "n"(SC), "n"(HA), "n"(HB));
}

template <int O, int SC, uint32_t HA = HI_SW, uint32_t HB = HI_SW, int SZ>
__device__ __forceinline__ void wg64_ss(float (&d)[SZ], uint32_t da, uint32_t db) {
  asm volatile("{ .reg .pred p; .reg .b32 h, k; .reg .b64 a, b; setp.ne.b32 p, %34, 0; mov.b32 h, %35; mov.b32 k, %36; mov.b64 a, {%32, h}; mov.b64 b, {%33, k};\n"
    "wgmma.mma_async.sync.aligned.m64n64k16.f32.bf16.bf16 {%0,%1,%2,%3,%4,%5,%6,%7,%8,%9,%10,%11,%12,%13,%14,%15,%16,%17,%18,%19,%20,%21,%22,%23,%24,%25,%26,%27,%28,%29,%30,%31}, a, b, p, 1, 1, 0, 1; }"
    : R8(d, O + 0), R8(d, O + 8), R8(d, O + 16), R8(d, O + 24) : "r"(da), "r"(db), "n"(SC), "n"(HA), "n"(HB));
}

template <int O, int SC, uint32_t HA = HI_SW, uint32_t HB = HI_SW, int SZ>
__device__ __forceinline__ void wg64_ss_tt(float (&d)[SZ], uint32_t da, uint32_t db) {
  asm volatile("{ .reg .pred p; .reg .b32 h, k; .reg .b64 a, b; setp.ne.b32 p, %34, 0; mov.b32 h, %35; mov.b32 k, %36; mov.b64 a, {%32, h}; mov.b64 b, {%33, k};\n"
    "wgmma.mma_async.sync.aligned.m64n64k16.f32.bf16.bf16 {%0,%1,%2,%3,%4,%5,%6,%7,%8,%9,%10,%11,%12,%13,%14,%15,%16,%17,%18,%19,%20,%21,%22,%23,%24,%25,%26,%27,%28,%29,%30,%31}, a, b, p, 1, 1, 1, 1; }"
    : R8(d, O + 0), R8(d, O + 8), R8(d, O + 16), R8(d, O + 24) : "r"(da), "r"(db), "n"(SC), "n"(HA), "n"(HB));
}

template <int O, int SC, uint32_t HA = HI_SW, uint32_t HB = HI_SW, int SZ>
__device__ __forceinline__ void wg8_ss_tn(float (&d)[SZ], uint32_t da, uint32_t db) {
  asm volatile("{ .reg .pred p; .reg .b32 h, k; .reg .b64 a, b; setp.ne.b32 p, %6, 0; mov.b32 h, %7; mov.b32 k, %8; mov.b64 a, {%4, h}; mov.b64 b, {%5, k};\n"
    "wgmma.mma_async.sync.aligned.m64n8k16.f32.bf16.bf16 {%0,%1,%2,%3}, a, b, p, 1, 1, 1, 0; }"
    : "+f"(d[O + 0]), "+f"(d[O + 1]), "+f"(d[O + 2]), "+f"(d[O + 3]) : "r"(da), "r"(db), "n"(SC), "n"(HA), "n"(HB));
}

template <int O, int SC, uint32_t HB, int SZ>
__device__ __forceinline__ void wg128_rs(float (&d)[SZ], uint32_t a0, uint32_t a1, uint32_t a2, uint32_t a3, uint32_t db) {
  asm volatile("{ .reg .pred p; .reg .b32 k; .reg .b64 b; setp.ne.b32 p, %69, 0; mov.b32 k, %70; mov.b64 b, {%68, k};\n"
    "wgmma.mma_async.sync.aligned.m64n128k16.f32.bf16.bf16 {%0,%1,%2,%3,%4,%5,%6,%7,%8,%9,%10,%11,%12,%13,%14,%15,%16,%17,%18,%19,%20,%21,%22,%23,%24,%25,%26,%27,%28,%29,%30,%31,%32,%33,%34,%35,%36,%37,%38,%39,%40,%41,%42,%43,%44,%45,%46,%47,%48,%49,%50,%51,%52,%53,%54,%55,%56,%57,%58,%59,%60,%61,%62,%63}, {%64,%65,%66,%67}, b, p, 1, 1, 0; }"
    : R8(d, O + 0), R8(d, O + 8), R8(d, O + 16), R8(d, O + 24), R8(d, O + 32), R8(d, O + 40), R8(d, O + 48), R8(d, O + 56) : "r"(a0), "r"(a1), "r"(a2), "r"(a3), "r"(db), "n"(SC), "n"(HB));
}

template <int O, int SC, uint32_t HB, int SZ>
__device__ __forceinline__ void wg112_rs(float (&d)[SZ], uint32_t a0, uint32_t a1, uint32_t a2, uint32_t a3, uint32_t db) {
  asm volatile("{ .reg .pred p; .reg .b32 k; .reg .b64 b; setp.ne.b32 p, %61, 0; mov.b32 k, %62; mov.b64 b, {%60, k};\n"
    "wgmma.mma_async.sync.aligned.m64n112k16.f32.bf16.bf16 {%0,%1,%2,%3,%4,%5,%6,%7,%8,%9,%10,%11,%12,%13,%14,%15,%16,%17,%18,%19,%20,%21,%22,%23,%24,%25,%26,%27,%28,%29,%30,%31,%32,%33,%34,%35,%36,%37,%38,%39,%40,%41,%42,%43,%44,%45,%46,%47,%48,%49,%50,%51,%52,%53,%54,%55}, {%56,%57,%58,%59}, b, p, 1, 1, 0; }"
    : R8(d, O + 0), R8(d, O + 8), R8(d, O + 16), R8(d, O + 24), R8(d, O + 32), R8(d, O + 40), R8(d, O + 48) : "r"(a0), "r"(a1), "r"(a2), "r"(a3), "r"(db), "n"(SC), "n"(HB));
}

template <int O, int SC, uint32_t HB, int SZ>
__device__ __forceinline__ void wg24_rs(float (&d)[SZ], uint32_t a0, uint32_t a1, uint32_t a2, uint32_t a3, uint32_t db) {
  asm volatile("{ .reg .pred p; .reg .b32 k; .reg .b64 b; setp.ne.b32 p, %17, 0; mov.b32 k, %18; mov.b64 b, {%16, k};\n"
    "wgmma.mma_async.sync.aligned.m64n24k16.f32.bf16.bf16 {%0,%1,%2,%3,%4,%5,%6,%7,%8,%9,%10,%11}, {%12,%13,%14,%15}, b, p, 1, 1, 0; }"
    : R8(d, O + 0), "+f"(d[O + 8]), "+f"(d[O + 9]), "+f"(d[O + 10]), "+f"(d[O + 11]) : "r"(a0), "r"(a1), "r"(a2), "r"(a3), "r"(db), "n"(SC), "n"(HB));
}

template <int O, int SC, uint32_t HB, int SZ>
__device__ __forceinline__ void wg128_rs_t(float (&d)[SZ], uint32_t a0, uint32_t a1, uint32_t a2, uint32_t a3, uint32_t db) {
  asm volatile("{ .reg .pred p; .reg .b32 k; .reg .b64 b; setp.ne.b32 p, %69, 0; mov.b32 k, %70; mov.b64 b, {%68, k};\n"
    "wgmma.mma_async.sync.aligned.m64n128k16.f32.bf16.bf16 {%0,%1,%2,%3,%4,%5,%6,%7,%8,%9,%10,%11,%12,%13,%14,%15,%16,%17,%18,%19,%20,%21,%22,%23,%24,%25,%26,%27,%28,%29,%30,%31,%32,%33,%34,%35,%36,%37,%38,%39,%40,%41,%42,%43,%44,%45,%46,%47,%48,%49,%50,%51,%52,%53,%54,%55,%56,%57,%58,%59,%60,%61,%62,%63}, {%64,%65,%66,%67}, b, p, 1, 1, 1; }"
    : R8(d, O + 0), R8(d, O + 8), R8(d, O + 16), R8(d, O + 24), R8(d, O + 32), R8(d, O + 40), R8(d, O + 48), R8(d, O + 56) : "r"(a0), "r"(a1), "r"(a2), "r"(a3), "r"(db), "n"(SC), "n"(HB));
}

template <int O, int SC, uint32_t HB, int SZ>
__device__ __forceinline__ void wg8_rs(float (&d)[SZ], uint32_t a0, uint32_t a1, uint32_t a2, uint32_t a3, uint32_t db) {
  asm volatile("{ .reg .pred p; .reg .b32 k; .reg .b64 b; setp.ne.b32 p, %9, 0; mov.b32 k, %10; mov.b64 b, {%8, k};\n"
    "wgmma.mma_async.sync.aligned.m64n8k16.f32.bf16.bf16 {%0,%1,%2,%3}, {%4,%5,%6,%7}, b, p, 1, 1, 0; }"
    : "+f"(d[O + 0]), "+f"(d[O + 1]), "+f"(d[O + 2]), "+f"(d[O + 3]) : "r"(a0), "r"(a1), "r"(a2), "r"(a3), "r"(db), "n"(SC), "n"(HB));
}

template <int V> struct IC { static constexpr int v = V; };
template <int I, int N, class Fn> __device__ __forceinline__ void sfor(Fn&& f) {
  if constexpr (I < N) { f(IC<I>{}); sfor<I + 1, N>(f); }
}
#define LAM(X) [&](auto X) __attribute__((always_inline))
#define INL __attribute__((always_inline))

__host__ __device__ constexpr uint32_t LBO(uint32_t b) { return (b >> 4) << 16; }
constexpr float LOG2E = 1.4426950408889634f, LN2 = 0.6931471805599453f;
#define EARLY 0
#define CSWAIT 0
#define QFWAIT 4
#define ST1 3
#define TSW 9
#define KSCHED 2
#define PACE 200
#define P1WIN 3

__host__ __device__ constexpr int slotB(int c) { return c & 3; }
__host__ __device__ constexpr int parB(int c) { return c >> 2; }
__host__ __device__ constexpr int slotC(int c) { return (int)((0x41034210u >> (4 * c)) & 7); }
__host__ __device__ constexpr int parC(int c) { return c >= 5; }
__host__ __device__ constexpr int slotM(int m) { return (int)((0x98ba3198bacd98baull >> (4 * m)) & 15); }
__host__ __device__ constexpr int parM(int m) { return (0x3f03 >> m) & 1; }
__host__ __device__ constexpr int tileM(int m) { return (0xfa48 >> m) & 1; }
__host__ __device__ constexpr int partM(int m) { return (int)((0x2211023213130030ull >> (4 * m)) & 15); }
__host__ __device__ constexpr int peerM(int m) { return (0xa4dc >> m) & 1; }
__host__ __device__ constexpr int slotA(int part, int peer) { return ((peer ? 0x3751 : 0x2640) >> (4 * part)) & 15; }

struct alignas(64) Params {
  CUtensorMap map[9];
  uint32_t zero;
  uint32_t jobs[48];
};

#define TS(role, k)
#define TSG(role, k)

__device__ __forceinline__ float phi(float u, float rs, float rl) {
  return fmaxf(add_sat(ex2(u * rl), 1e-6f), fmaf(u, rs, 1.000001f));
}
__device__ __forceinline__ float mish(float u, float rs, float rl) {
  const float v = ex2(fmaf(u, rl, -0.5f)), h = u * rs;
  return fmaf(-h, rcp(fmaf(v, v + 1.41421356237f, 1.f)), h);
}
__device__ __forceinline__ uint32_t split(float& v) { const uint32_t h = pack(v, 0.f); v -= bflo(h); return h; }

__device__ __forceinline__ bool fresh(const float4& a, uint32_t tag) {
  return !(((__float_as_uint(a.x) ^ tag) | (__float_as_uint(a.y) ^ tag) | (__float_as_uint(a.z) ^ tag) | (__float_as_uint(a.w) ^ tag)) & 1);
}
__device__ __forceinline__ uint32_t kvpart(int h, int lane) { return 8192 + (lane >> 1) * 128 + (((2 * h + (lane & 1)) ^ ((lane >> 1) & 7)) << 4); }
__device__ __forceinline__ void add8(float (&s)[8], const uint4& v) {
  s[0] += bflo(v.x); s[1] += bfhi(v.x); s[2] += bflo(v.y); s[3] += bfhi(v.y);
  s[4] += bflo(v.z); s[5] += bfhi(v.z); s[6] += bflo(v.w); s[7] += bfhi(v.w);
}

__global__ void __cluster_dims__(2, 1, 1) __launch_bounds__(384, 1)
fused_kernel(const __grid_constant__ Params prm, const __nv_bfloat16* __restrict__ x, const __nv_bfloat16* __restrict__ wqkv,
             const __nv_bfloat16* __restrict__ wo, const __nv_bfloat16* __restrict__ w1, const __nv_bfloat16* __restrict__ b1,
             const __nv_bfloat16* __restrict__ w2, __nv_bfloat16* __restrict__ out) {
  extern __shared__ __align__(1024) uint8_t smem_raw[];
  const uint32_t sb = __reduce_max_sync(0xffffffffu, (uint32_t)__cvta_generic_to_shared(smem_raw));
  const int i = blockIdx.x >> 3, j = blockIdx.x & 7;
  const int warp = __reduce_max_sync(0xffffffffu, threadIdx.x >> 5);
  const int lane = threadIdx.x & 31;
  uint32_t left = 1u << 16;

  TS(threadIdx.x >> 7, 0);
  TSG(threadIdx.x >> 7, 62);
  if (warp == 8) {
    if (lane == 0) {
#pragma unroll
      for (int c = 0; c < P1WIN; c++) mbar_init(sb + B_FULL + 8 * c, 1);
      asm volatile("fence.mbarrier_init.release.cluster;" ::: "memory");
    }
    __syncwarp();
#pragma unroll
    for (int c = 0; c < P1WIN; c++) p1_load_elect(sb + B_FULL + 8 * c, sb + c * SLOT, &prm.map[5], 64 * c, 128 * i, sb + (8 + c) * SLOT, &prm.map[6], 64 * j);
    TS(2, 44);
  } else if (warp < 8) {
    if (lane == 0) {
      if (warp >= P1WIN) mbar_init(sb + MISC + 8 * warp, 1);
#pragma unroll
      for (int k = 1; k < 5; k++) mbar_init(sb + MISC + 64 * k + 8 * warp, k < 3 ? (k == 1 && warp == 7 ? 2 : 1) : (k == 3 ? 8 : 4));
      asm volatile("fence.mbarrier_init.release.cluster;" ::: "memory");
    }
  } else if (warp == 9) {
    if (lane < 16) sts128(sb + ONES + lane * 16, 0x3f803f80u, 0x3f803f80u, 0x3f803f80u, 0x3f803f80u);
    fence_async();
  }
  TS(threadIdx.x >> 7, 41);
  __syncthreads();
  asm volatile("barrier.cluster.arrive.relaxed.aligned;" ::: "memory");
  TS(threadIdx.x >> 7, 42);

  if (warp >= 8) {
    asm volatile("setmaxnreg.dec.sync.aligned.u32 72;");
    auto gather = [&](const float4* p, int stride, uint32_t* ex) INL {
      float4 a, b, c;
      int it = 0;
      while (true) {
        a = ld_rlx128f(p); b = ld_rlx128f(p + stride); c = ld_rlx128f(p + 2 * stride);
        if (__all_sync(0xffffffffu, a.w == 32.f && b.w == 32.f && c.w == 32.f) || ++it > SPIN_LIMIT) break;
        __nanosleep(32);
      }
      float v[8] = {a.x, a.y, a.z, b.x, b.y, b.z, c.x, c.y};
#pragma unroll
      for (int k = 0; k < 8; k++) { const uint32_t h = split(v[k]); ex[k] = h | pack(0.f, v[k]); }
    };
    if (warp <= 9) {
      if (warp == 9) {
        if (lane == 0) {
#pragma unroll
          for (int k = 0; k < 8; k++) mbar_expect_tx(sb + B_AF + 8 * k, 8192);
#pragma unroll
          for (int k = 0; k < 5; k++) prefetch_map(&prm.map[k]);
        }
        const float4* const sum = &g_sum[((ld_rlx32(&g_epoch[blockIdx.x]) & 1) * 8 + j) * NSUM];
#pragma unroll 1
        for (int c = 0; c < 8; c++) {
          mbar_wait(sb + B_FULL + 8 * c, 0, left);
          if (lane == 0) tma2d_store(&prm.map[7], 64 * c, 128 * i + 16 * j, sb + c * SLOT + 2048 * j);
          if (c == 4) {
            uint32_t ex[8];
            gather(sum + SUM_KV + (lane & 15), 16, ex);
            if (lane < 16) {
#pragma unroll
              for (int k = 0; k < 8; k++) sts128(sb + EXT + lane * 144 + 16 * k, ex[k], 0, 0, 0);
            }
            fence_async();
            __syncwarp();
            if (lane == 0) mbar_arrive_n(sb + B_CS1, 4);
            TS(2, 13);
          }
        }
        if (lane == 0) {
          bulk_commit();
          prefetch_map(&prm.map[8]);
          bulk_wait();
          mbar_arrive_n(sb + B_CS2, 2);
          TS(2, 52);
        }
        mbar_wait(sb + B_FULL + 8 * 8, 0, left);
      }
      if (lane == 0) {
        if (warp == 8) {
#pragma unroll 1
          for (int c = P1WIN - 1; c < 8; c++) {
            const uint32_t bar = sb + B_FULL + 8 * c, live = c >= P1WIN;
            mbar_wait(live ? bar - 8 * P1WIN : sb + B_OUT, !live, left);
            p1_load_x(live, bar, sb + c * SLOT, &prm.map[5], 64 * c, 128 * i);
            mbar_wait(sb + (c < 4 ? B_OUT : B_EMPTY + 8 * (c & 3)), c < 4, left);
            p1_load_w(live, bar, sb + (8 + (c & 3)) * SLOT, &prm.map[6], 64 * j, 64 * c);
            TS(2, 44 + c);
          }
        }
#pragma unroll 1
        for (int n = warp == 8 ? 0 : 28; n < (warp == 8 ? 28 : 48); n++) {
          const uint32_t job = prm.jobs[n];
          const uint32_t slot = (job >> 6) & 15, mp = (job >> 12) & 7, c = (job >> 15) & 7;
          const uint32_t bar = sb + B_FULL + 8 * slot;
          const int jj = j ^ (job >> 20);
          const int u = (mp == 0 || mp == 4) ? 64 * jj : FS * jj + 64 * ((job >> 18) & 3);
          if ((job & 31) != 31) mbar_wait(sb + MISC + 8 * (job & 31), (job >> 5) & 1, left);
          if (job & 2048) mbar_expect_tx(bar, mp == 3 ? 12288 : SLOT);
          tma3d(sb + slot * SLOT + (job & 1024) * 8, &prm.map[mp], mp < 2 ? u : 0, mp < 2 ? 64 * c : u, mp < 2 ? 0 : 4 * (j & 1) + 2 * (((j >> 1) ^ c) & 1), bar);
        }
      }
    } else {
      const uint32_t epoch = ld_rlx32(&g_epoch[blockIdx.x]), par = epoch & 1;
      float4* const sum = &g_sum[(par * 8 + j) * NSUM];
      uint32_t ex[8];
      const int row0 = 32 * i + 16 * (warp - 10), f0 = FS * j + 8 * (lane - 8);
      const bool on = lane < 30 && f0 < F_;
      if (CSWAIT >= 0) mbar_wait(sb + B_FULL + 8 * CSWAIT, 0, left);
      if (lane < 17) g_sum[((par ^ 1) * 8 + j) * NSUM + i * 34 + (warp - 10) * 17 + lane] = make_float4(0.f, 0.f, 0.f, 0.f);
      {
        const int ld2 = lane < 8 ? 3 * D_ : F_;
        const __nv_bfloat16* src = wqkv + (size_t)(row0 + (lane >> 4)) * (3 * D_) + D_ + ((lane >> 3) & 1) * D_ + 64 * j + 8 * (lane & 7);
        const __nv_bfloat16* src2 = (lane < 8 ? wqkv + 64 * j + 8 * lane : w1 + (on ? f0 : FS * j)) + (size_t)row0 * ld2;
        int ld = 6 * D_;
        float s[8] = {0.f, 0.f, 0.f, 0.f, 0.f, 0.f, 0.f, 0.f};
#pragma unroll 1
        for (int b = 0; b < 3; b++) {
          uint4 v[8];
#pragma unroll
          for (int k = 0; k < 8; k++) v[k] = ldg_nc128(src + k * ld);
#pragma unroll
          for (int k = 0; k < 8; k++) add8(s, v[k]);
          if (b != 1) {
#pragma unroll
            for (int k = 0; k < 8; k++) { const float o = __shfl_xor_sync(0xffffffffu, s[k], 16); s[k] = b == 0 ? s[k] + o : (on ? s[k] : 0.f); }
            const int stride = b == 0 ? 16 : 32;
            float4* dst = sum + (b == 0 ? SUM_KV : SUM_QF) + lane;
            if (lane < stride) { red128f(dst, s[0], s[1], s[2], 1.f); red128f(dst + stride, s[3], s[4], s[5], 1.f); red128f(dst + 2 * stride, s[6], s[7], 0.f, 1.f); }
#pragma unroll
            for (int k = 0; k < 8; k++) s[k] = 0.f;
            TS(2, 9 + (b >> 1));
          }
          if (b == 0) mbar_wait(sb + B_FULL + 8 * QFWAIT, 0, left);
          src = b == 0 ? src2 : src + 8 * ld;
          ld = ld2;
        }
      }
      if (warp == 11) {
        const uint4 bv = on && lane >= 8 ? ldg_nc128(b1 + f0) : make_uint4(0, 0, 0, 0);
        gather(sum + SUM_QF + lane, 32, ex);
        TS(2, 18);
        const uint32_t bw[4] = {bv.x, bv.y, bv.z, bv.w};
        const uint32_t e = sb + EXT + (lane & 15) * 144;
        mbar_wait(sb + B_CS1, 0, left);
#pragma unroll
        for (int k = 0; k < 8; k++) {
          sts32(e + 16 * k + 4 + 4 * (lane >> 4), ex[k]);
          sts16(e + 16 * k + 12 + 2 * (lane >> 4), bw[k >> 1] >> (16 * (k & 1)));
        }
        fence_async();
        __syncwarp();
        if (lane == 0) mbar_arrive_n(sb + B_CS2, 2);
        TS(2, 15);
      }
      {
        mbar_wait(sb + B_KVPART, 0, left);
        TS(2, 12);
        float4 a[6];
#pragma unroll
        for (int h = 0; h < 2; h++) {
          const uint32_t kp = sb + 12 * SLOT + kvpart(2 * (warp - 10) + h, lane);
#pragma unroll
          for (int q = 0; q < 3; q++) {
            const float4 u = lds128f(kp + 2048 * q), v = lds128f(kp + SLOT + 2048 * q);
            a[3 * h + q] = make_float4(u.x + v.x, u.y + v.y, u.z + v.z, 1.f);
          }
        }
#pragma unroll
        for (int q = 0; q < 6; q++) red128f(sum + (warp - 10) * 192 + 32 * q + lane, a[q].x, a[q].y, a[q].z, 1.f);
        __syncwarp();
        if (lane == 0) mbar_arrive(sb + B_KVFREE);
        TS(2, 11);
      }
      {
        const float4* kvp = sum + (warp - 10) * 192 + lane;
        float4 v[6];
        int it = 0;
        while (true) {
          bool done = true;
#pragma unroll
          for (int k = 0; k < 6; k++) v[k] = ld_rlx128f(kvp + 32 * k);
#pragma unroll
          for (int k = 0; k < 6; k++) done = done && v[k].w == 16.f;
          if (__all_sync(0xffffffffu, done) || ++it > SPIN_LIMIT) break;
        }
#pragma unroll
        for (int h = 0; h < 2; h++) {
          const float4 a = v[3 * h], b = v[3 * h + 1], c = v[3 * h + 2];
          const int zl = 8 * (lane & 3);
          const float z0 = __shfl_sync(0xffffffffu, c.z, zl), z1 = __shfl_sync(0xffffffffu, c.z, zl + 4);
          const float z2 = __shfl_sync(0xffffffffu, c.z, zl + 1), z3 = __shfl_sync(0xffffffffu, c.z, zl + 5);
          const uint32_t d = sb + KVS + (2 * (warp - 10) + h) * 768 + lane * 4;
          sts32(d, pack(a.x, a.y)); sts32(d + 256, pack(a.z, b.x)); sts32(d + 128, pack(b.y, b.z)); sts32(d + 384, pack(c.x, c.y));
          sts32(d + 512, pack(z0, z1)); sts32(d + 640, pack(z2, z3));
        }
        fence_async();
        __syncwarp();
        if (lane == 0) mbar_arrive_n(sb + B_KVRDY, 2);
        TS(2, 14);
      }
      if (warp == 10 && lane == 0) {
        mbar_wait(sb + B_CS2, 0, left);
        fence_async_all();
        asm volatile("red.release.gpu.global.add.u32 [%0], 1;" ::"l"(&g_flag[i * 32]) : "memory");
        TS(2, 55);
        const unsigned target = 8u * (epoch + 1);
        int it = 0;
        while (true) {
          unsigned v;
          asm volatile("ld.acquire.gpu.global.u32 %0, [%1];" : "=r"(v) : "l"(&g_flag[i * 32]) : "memory");
          if ((int)(v - target) >= 0 || ++it > SPIN_LIMIT) break;
          __nanosleep(128);
        }
        fence_async_all();
        mbar_arrive(sb + B_OUT);
        TS(2, 16);
      }
    }
  } else {
    asm volatile("setmaxnreg.inc.sync.aligned.u32 216;");
    const int w = warp >> 2, wq = warp & 3, t = lane & 3;
    const uint32_t epoch = ld_rlx32(&g_epoch[blockIdx.x]);
    uint32_t dB = ((sb & 0x3ffffu) >> 4) + LBO(8192);
    uint32_t dA = dB + (LBO(16) - LBO(8192) + w * 512);
    constexpr uint32_t TO_NS = LBO(128) - LBO(8192), TO_EX = 0u - LBO(8192);
    auto release = [&](uint32_t bar) INL { if (lane == 0) mbar_arrive(sb + bar); };
    auto next = [&]() INL { dA += prm.zero; dB += prm.zero; wg_fence(); };

    float acc1[64];
    uint32_t ea[4];
    float rs0, rs1, rl0, rl1;
    const uint32_t stm = sb + (12 + w) * SLOT + (16 * wq + (lane & 15)) * 128 + (((lane >> 4) ^ (lane & 7)) << 4);
    const uint32_t sta = stm - 12 * SLOT - w * 8192;
    uint4 xr[4];
    const uint32_t tag = (epoch + 1) & 1;
    float4* const stp = &g_st[(i * 8 + warp) * 8];
    float4 sv;
    const uint32_t zr = prm.zero;
    uint32_t klo = 0x10000u, khi = 0xffff0000u;
    bool ok = false;
    sfor<0, 8>(LAM(C) {
      constexpr int c = C.v;
      if (!ok) mbar_wait(sb + B_FULL + 8 * c, 0, left);
      TS(w, 1 + c);
      next();
      sfor<0, 4>(LAM(K) { wg128_ss<0, (c | K.v) != 0>(acc1, dA + c * 1024 + K.v * 2, dB + (8 + (c & 3)) * 1024 + K.v * 128); });
      wg_commit();
      if constexpr (c > 0) { wg_wait<1>(); release(B_EMPTY + 8 * ((c - 1) & 3)); }
      if constexpr (c == 0) {
#pragma unroll
        for (int k = 0; k < 4; k++) xr[k] = ldg_nc128(x + (size_t)(128 * i + 16 * warp + 8 * (lane >> 4) + j) * D_ + 8 * (lane & 15) + 128 * k);
      }
      if constexpr (c == ST1) ok = mbar_test(sb + B_FULL + 8 * (c + 1), 0, klo, khi, zr);
      else ok = mbar_test(sb + B_FULL + 8 * (c + 1), 0);
      if constexpr (c == ST1) {
        float xv[32], s[4] = {0.f, 0.f, 0.f, 0.f};
#pragma unroll
        for (int k = 0; k < 4; k++) {
          const uint32_t u[4] = {xr[k].x, xr[k].y, xr[k].z, xr[k].w};
#pragma unroll
          for (int e = 0; e < 4; e++) {
            xv[8 * k + 2 * e] = __uint_as_float(u[e] * klo); xv[8 * k + 2 * e + 1] = __uint_as_float(u[e] & khi);
            s[e] += xv[8 * k + 2 * e] + xv[8 * k + 2 * e + 1];
          }
        }
        float mu = (s[0] + s[1]) + (s[2] + s[3]);
#pragma unroll
        for (int o = 1; o < 16; o *= 2) mu += __shfl_xor_sync(0xffffffffu, mu, o);
        mu *= -1.f / D_;
        s[0] = s[1] = s[2] = s[3] = 0.f;
#pragma unroll
        for (int k = 0; k < 32; k++) { const float d = xv[k] + mu; s[k & 3] = fmaf(d, d, s[k & 3]); }
        float q = (s[0] + s[1]) + (s[2] + s[3]);
#pragma unroll
        for (int o = 1; o < 16; o *= 2) q += __shfl_xor_sync(0xffffffffu, q, o);
        q = sqrt_(fmaf(q, 1.f / D_, 1e-5f));
        if ((lane & 15) == 0) st_rlx64((uint2*)(stp + j) + (lane >> 4), (__float_as_uint(mu) & ~1u) | tag, (__float_as_uint(q) & ~1u) | tag);
      }
      if constexpr (c == 6) sv = ld_rlx128f(stp + (lane >> 2));
      if constexpr (c == 7) {
        int it = 0;
        while (!__all_sync(0xffffffffu, fresh(sv, tag)) && ++it < SPIN_LIMIT) sv = ld_rlx128f(stp + (lane >> 2));
        TS(w, 43);
        rs0 = rcp(sv.y); rs1 = rcp(sv.w);
        rl0 = rs0 * LOG2E; rl1 = rs1 * LOG2E;
#pragma unroll
        for (int r = 0; r < 2; r++) {
          float v = t < 3 ? (r ? sv.z : sv.x) : (r ? sv.w : sv.y);
          const uint32_t h0 = split(v), h1 = split(v), m = t < 3 ? 0x10001u : 1u;
          ea[r] = h0 * m;
          ea[2 + r] = h1 * m;
        }
      }
    });
    auto phi16 = [&](auto O, auto& acc, uint32_t* r) INL {
      constexpr int o = O.v;
      reg_fence<o, 8>(acc);
#pragma unroll
      for (int k = 0; k < 4; k++) r[k] = pack(phi(acc[o + 2 * k], k & 1 ? rs1 : rs0, k & 1 ? rl1 : rl0), phi(acc[o + 2 * k + 1], k & 1 ? rs1 : rs0, k & 1 ? rl1 : rl0));
    };

    float acc2[64], kva[32], za[4];
    sfor<0, 8>(LAM(C) {
      constexpr int c = C.v;
      if (!ok) mbar_wait(sb + B_FULL + 8 * (8 + slotB(c)), parB(c), left);
      TS(w, 9 + c);
      next();
      constexpr int ce = 4 - KSCHED;
      if constexpr (c == ce + 1) {
        const uint32_t dk = dB + 12 * 1024 + w * 1024;
        sfor<0, 4>(LAM(K) { wg64_ss_tt<0, K.v != 0>(kva, dk + 512 + K.v * 128, dk + K.v * 128); });
        sfor<0, 4>(LAM(K) { wg8_ss_tn<0, K.v != 0, HI_SW, HI_NS>(za, dk + K.v * 128, dB + (TO_NS + (ONES >> 4))); });
      }
      sfor<0, 4>(LAM(K) { wg128_ss<0, (c | K.v) != 0>(acc2, dA + c * 1024 + K.v * 2, dB + (8 + slotB(c)) * 1024 + K.v * 128); });
      wg_commit();
      constexpr bool early = EARLY || c < 2 || c > ce;
      if constexpr (early) { wg_wait<1>(); release(B_EMPTY + 8 * slotB(c + 3)); }
      if constexpr (c == 0) {
        mbar_wait(sb + B_CS1, 0, left);
        TS(w, 40);
        const uint32_t m = t == 0;
        uint32_t e0 = ea[0] * m, e1 = ea[1] * m, e2 = ea[2] * m, e3 = ea[3] * m;
        pin(e0); pin(e1); pin(e2); pin(e3);
        wg_fence();
        wg128_rs<0, 1, HI_EX>(acc1, e0, e1, e2, e3, dB + (TO_EX + (EXT >> 4)));
        wg_commit();
      }
      if constexpr (c >= 2 && c <= ce) ok = mbar_test(sb + B_FULL + 8 * (8 + slotB(c + 1)), parB(c + 1), rs0, rs1, zr);
      else if constexpr (c < 7) ok = mbar_test(sb + B_FULL + 8 * (8 + slotB(c + 1)), parB(c + 1));
      if constexpr (c == 1) reg_fence<0, 64>(acc1);
      if constexpr (c >= 1 && c <= ce) {
        constexpr int k0 = KSCHED == 0 ? c - 1 : 2 * c - 2, k1 = KSCHED == 0 ? c : (c < 3 ? 2 * c : 0);
        constexpr int v0 = KSCHED == 1 ? 0 : k0, v1 = KSCHED == 1 ? (c == 3 ? 4 : 0) : k1;
        sfor<k0, k1>(LAM(U) {
          uint32_t r[4];
          phi16(IC<8 * U.v>{}, acc1, r);
          stsm4(stm ^ (U.v << 5), r[0], r[1], r[2], r[3]);
        });
        sfor<v0, v1>(LAM(U) {
          constexpr int o = 32 + 8 * U.v;
          stsm4((stm ^ (U.v << 5)) + 8192, pack(acc1[o] * rs0, acc1[o + 1] * rs0), pack(acc1[o + 2] * rs1, acc1[o + 3] * rs1),
                pack(acc1[o + 4] * rs0, acc1[o + 5] * rs0), pack(acc1[o + 6] * rs1, acc1[o + 7] * rs1));
        });
      }
      if constexpr (c == ce) { fence_async(); bar_wg(1 + w); }
      if constexpr (c == ce + 2) {
        reg_fence<0, 32>(kva);
        reg_fence<0, 4>(za);
        const uint32_t kp = sb + (12 + w) * SLOT + kvpart(wq, lane);
        const float z = t == 0 ? za[0] : (t == 1 ? za[2] : 0.f);
        sfor<0, 4>(LAM(H) {
          constexpr int h = H.v;
          if (wq == h) {
            sts128f(kp, kva[8 * h], kva[8 * h + 1], kva[8 * h + 2], 0.f);
            sts128f(kp + 2048, kva[8 * h + 3], kva[8 * h + 4], kva[8 * h + 5], 0.f);
            sts128f(kp + 4096, kva[8 * h + 6], kva[8 * h + 7], z, 0.f);
          }
        });
        __syncwarp();
        release(B_KVPART);
      }
      if constexpr (!early) { wg_wait<1>(); release(B_EMPTY + 8 * slotB(c + 3)); }
    });
    mbar_wait(sb + B_CS2, 0, left);
    TS(w, 39);
    {
      const uint32_t m = t & 1, n = t == 3 ? 0x10000u : t >> 1;
      uint32_t e0 = ea[0] * m, e1 = ea[1] * m, e2 = ea[2] * m, e3 = ea[3] * m;
      pin(e0); pin(e1); pin(e2); pin(e3);
      next();
      wg128_rs<0, 1, HI_EX>(acc2, e0, e1, e2, e3, dB + (TO_EX + (EXT >> 4)));
      wg_commit();
#pragma unroll
      for (int k = 0; k < 4; k++) { ea[k] *= n; pin(ea[k]); }
    }
    ok = mbar_test(sb + B_FULL + 8 * (8 + slotC(0)), parC(0));

    float acc3[56], acco[48];
    uint32_t pq[16];
    const uint32_t rows = (64 * w + 16 * wq) * 128;
    const uint32_t peer = __reduce_max_sync(0xffffffffu, mapa(sb, (j & 1) ^ 1));
    auto mish16 = [&](auto O, auto& acc, int part, int a) INL {
      constexpr int o = O.v;
      uint32_t r[4];
      reg_fence<o, 8>(acc);
#pragma unroll
      for (int k = 0; k < 4; k++) r[k] = pack(mish(acc[o + 2 * k], k & 1 ? rs1 : rs0, k & 1 ? rl1 : rl0), mish(acc[o + 2 * k + 1], k & 1 ? rs1 : rs0, k & 1 ? rl1 : rl0));
      stsm4((sta ^ (a << 5)) + slotA(part, 0) * SLOT, r[0], r[1], r[2], r[3]);
    };
    auto send = [&](int part, int pf) INL {
      fence_async();
      if (pf >= 0) mbar_wait(sb + B_PF + pf * 16 + w * 8, 0, left);
      bulk_peer_elect(peer + slotA(part, 1) * SLOT + rows, sb + slotA(part, 0) * SLOT + rows, 2048, peer + B_AF + part * 16 + w * 8);
    };
    asm volatile("barrier.cluster.wait.aligned;" ::: "memory");
    sfor<0, 8>(LAM(C) {
      constexpr int c = C.v;
      if (!ok) mbar_wait(sb + B_FULL + 8 * (8 + slotC(c)), parC(c), left);
      if constexpr (c == 6) { TS(w, 38); mbar_wait(sb + B_KVRDY, 0, left); }
      TS(w, 17 + c);
      next();
      if constexpr (c == 6)
        sfor<0, 4>(LAM(H) { constexpr int h = H.v; wg24_rs<12 * h, 0, HI_NS>(acco, pq[4 * h], pq[4 * h + 1], pq[4 * h + 2], pq[4 * h + 3], dB + (TO_NS + ((KVS + h * 768) >> 4))); });
      sfor<0, 4>(LAM(K) { wg112_ss<0, (c | K.v) != 0>(acc3, dA + c * 1024 + K.v * 2, dB + (8 + slotC(c)) * 1024 + K.v * 128); });
      if constexpr (c == 7) wg112_rs<0, 1, HI_EX>(acc3, ea[0], ea[1], ea[2], ea[3], dB + (TO_EX + (EXT >> 4)));
      wg_commit();
      if constexpr (c == 0 || c == 7) { wg_wait<1>(); release(B_EMPTY + 8 * (c == 0 ? slotB(7) : slotC(c == 0 ? 0 : c - 1))); }
      if constexpr (c == 7) release(B_EMPTY + 8 * 5);
      if constexpr (c == 0) ok = mbar_test(sb + B_FULL + 8 * (8 + slotC(c + 1)), parC(c + 1));
      else if constexpr (c < 7) ok = mbar_test(sb + B_FULL + 8 * (8 + slotC(c + 1)), parC(c + 1), rl0, rl1, zr);
      else ok = mbar_test(sb + B_FULL + 8 * slotM(0), parM(0));
      if constexpr (c == 0) reg_fence<0, 64>(acc2);
      constexpr int q0 = c == 0 ? 0 : (c < 3 ? c + 1 : 4), q1 = c < 3 ? c + 2 : 4;
      sfor<q0, q1>(LAM(N) { constexpr int n = N.v; phi16(IC<8 * n>{}, acc2, pq + 4 * n); pin2(zr, pq[4 * n], pq[4 * n + 1]); pin2(zr, pq[4 * n + 2], pq[4 * n + 3]); });
      if constexpr (c >= 3 && c < 7) { constexpr int a = (c - 3) & 3; mish16(IC<32 + 8 * a>{}, acc2, 0, a); }
      if constexpr (c == 6) send(0, 0);
      if constexpr (c == 7) {
        reg_fence<0, 48>(acco);
#pragma unroll
        for (int h = 0; h < 4; h++) {
          const float r0 = rcp(acco[12 * h + 8] + 1e-6f), r1 = rcp(acco[12 * h + 10] + 1e-6f);
          stsm4((sta ^ (h << 5)) + slotA(3, 0) * SLOT, pack(acco[12 * h] * r0, acco[12 * h + 1] * r0), pack(acco[12 * h + 2] * r1, acco[12 * h + 3] * r1),
                pack(acco[12 * h + 4] * r0, acco[12 * h + 5] * r0), pack(acco[12 * h + 6] * r1, acco[12 * h + 7] * r1));
        }
        send(3, -1);
      }
      if constexpr (c != 0 && c != 7) { wg_wait<1>(); release(B_EMPTY + 8 * slotC(c == 0 ? 0 : c - 1)); }
      if constexpr (c == 4) { if (lane == 0) mbar_arrive_peer(peer + B_PF + w * 8); }
    });

    float accX[64], accY[64];
    const uint32_t sto = (lane & 15) * 128 + (((lane >> 4) ^ (lane & 7)) << 4) + wq * 4096;
    auto store_tile = [&](float (&acc)[64], int tile, uint32_t slot) INL {
      const uint32_t st = sb + slot * SLOT + sto;
#pragma unroll
      for (int a = 0; a < 16; a += 2)
        stsm4((st ^ ((a & 7) << 4)) + (a >> 3) * 2048, pack(acc[4 * a], acc[4 * a + 1]), pack(acc[4 * a + 2], acc[4 * a + 3]),
              pack(acc[4 * a + 4], acc[4 * a + 5]), pack(acc[4 * a + 6], acc[4 * a + 7]));
      fence_async();
      tma3d_add_elect(&prm.map[8], 0, 128 * i + 64 * w + 16 * wq, 4 * (j & 1) + 2 * (((j >> 1) ^ tile) & 1), sb + slot * SLOT + wq * 4096);
    };
    sfor<0, 16>(LAM(M) {
      constexpr int m = M.v, part = partM(m), nk = part == 2 ? 3 : 4;
      if (!ok) mbar_wait(sb + B_FULL + 8 * slotM(m), parM(m), left);
      if constexpr (m == 2 || m == 4 || m == 7 || m == 10) mbar_wait(sb + B_AF + part * 16 + w * 8, 0, left);
      TS(w, 25 + m < 37 ? 25 + m : 33 + m);
      next();
      const uint32_t da = dA + slotA(part, peerM(m)) * 1024, db = dB + (LBO(part == 2 ? 6144 : 8192) - LBO(8192) + slotM(m) * 1024);
      sfor<0, nk>(LAM(K) {
        if constexpr (tileM(m)) wg128_ss<0, (m != 3 || K.v != 0)>(accY, da + K.v * 2, db + K.v * 128);
        else wg128_ss<0, (m | K.v) != 0>(accX, da + K.v * 2, db + K.v * 128);
      });
      wg_commit();
      if constexpr (m == 0) {
        wg_wait<1>();
        release(B_EMPTY + 8 * slotC(7));
        if (lane == 0) mbar_arrive_peer(peer + B_PF + 16 + w * 8);
        reg_fence<0, 56>(acc3);
      }
      if constexpr (m == 12) { wg_wait<2>(); reg_fence<0, 64>(accX); }
      if constexpr (m >= 1 && m < 7) ok = mbar_test(sb + B_FULL + 8 * slotM(m + 1), parM(m + 1), rl0, rl1, zr);
      else if constexpr (m < 15) ok = mbar_test(sb + B_FULL + 8 * slotM(m + 1), parM(m + 1));
      if constexpr (m < 7) mish16(IC<8 * m>{}, acc3, m < 4 ? 1 : 2, m & 3);
      if constexpr (m == 3 || m == 6) send(m == 3 ? 1 : 2, m == 3 ? 1 : -1);
      if constexpr (m == 10) { if (lane == 0) mbar_arrive_peer(peer + B_DONE); }
      if constexpr (m == 12) {
        mbar_wait(sb + B_EMPTY + 8 * (4 + w), w, left);
        mbar_wait(sb + B_OUT, 0, left);
        store_tile(accX, 0, 12 + w);
        TS(w, 49);
      }
      if constexpr (m != 0 && m != 11 && m != 12 && m != 15) wg_wait<1>();
      if constexpr ((m >= 1 && m <= 10) || m == 13) release(B_EMPTY + 8 * (slotM(m == 0 ? 0 : m - 1) - 8));
    });
    wg_wait<0>();
    reg_fence<0, 64>(accY);
    TS(w, 50);
    mbar_wait(sb + B_EMPTY + 8 * 2, 1, left);
    store_tile(accY, 1, 1 + 2 * w);
    TS(w, 51);
    bulk_wait_read();
    mbar_wait(sb + B_DONE, 0, left);
    if (threadIdx.x == 0) g_epoch[blockIdx.x] = epoch + 1;
    TS(w, 37);
    TSG(w, 63);
  }
}

typedef CUresult (*EncodeFn)(CUtensorMap*, CUtensorMapDataType, cuuint32_t, void*, const cuuint64_t*, const cuuint64_t*, const cuuint32_t*,
                             const cuuint32_t*, CUtensorMapInterleave, CUtensorMapSwizzle, CUtensorMapL2promotion, CUtensorMapFloatOOBfill);

bool encode(EncodeFn enc, CUtensorMap* m, const void* p, int rank, cuuint64_t d0, cuuint64_t d1, cuuint64_t d2, cuuint64_t s1, cuuint64_t s2,
            cuuint32_t b0, cuuint32_t b1, cuuint32_t b2) {
  cuuint64_t dims[3] = {d0, d1, d2}, strides[2] = {s1, s2};
  cuuint32_t box[3] = {b0, b1, b2}, es[3] = {1, 1, 1};
  return enc(m, CU_TENSOR_MAP_DATA_TYPE_BFLOAT16, rank, (void*)p, dims, strides, box, es, CU_TENSOR_MAP_INTERLEAVE_NONE, CU_TENSOR_MAP_SWIZZLE_128B,
             CU_TENSOR_MAP_L2_PROMOTION_L2_128B, CU_TENSOR_MAP_FLOAT_OOB_FILL_NONE) == CUDA_SUCCESS;
}

constexpr uint32_t job(uint32_t wait_bar, int parity, int slot, int half, int expect, int map, int c, int part, int peer = 0) {
  return (wait_bar ? (wait_bar - MISC) / 8 : 31) | parity << 5 | slot << 6 | half << 10 | expect << 11 | map << 12 | c << 15 | part << 18 | peer << 20;
}
constexpr uint32_t mjob(int ring, int parity, int m) {
  return job(ring < 0 ? 0 : B_EMPTY + 8 * ring, parity, slotM(m), 0, 1, partM(m) < 2 ? 2 : partM(m) + 1, tileM(m), partM(m) == 3 ? 0 : partM(m), peerM(m));
}

}

extern "C" void kernel_launch(void* const* d_in, const int* in_sizes, int n_in, void* d_out, int out_size) {
  const __nv_bfloat16* x = (const __nv_bfloat16*)d_in[0];
  const __nv_bfloat16* wqkv = (const __nv_bfloat16*)d_in[1];
  const __nv_bfloat16* wo = (const __nv_bfloat16*)d_in[2];
  const __nv_bfloat16* w1 = (const __nv_bfloat16*)d_in[4];
  const __nv_bfloat16* b1 = (const __nv_bfloat16*)d_in[5];
  const __nv_bfloat16* w2 = (const __nv_bfloat16*)d_in[6];
  static EncodeFn enc = nullptr;
  if (!enc) {
    void* fn = nullptr;
    cudaDriverEntryPointQueryResult st;
    if (cudaGetDriverEntryPoint("cuTensorMapEncodeTiled", &fn, cudaEnableDefault, &st) != cudaSuccess || !fn) return;
    enc = (EncodeFn)fn;
    cudaFuncSetAttribute(fused_kernel, cudaFuncAttributeMaxDynamicSharedMemorySize, SMEM_BYTES);
  }
  Params prm;
  bool ok = true;
  ok &= encode(enc, &prm.map[0], wqkv, 3, D_, D_, 1, 3 * D_ * 2, 3 * D_ * 2 * D_, 64, 64, 1);
  ok &= encode(enc, &prm.map[1], w1, 3, F_, D_, 1, F_ * 2, F_ * 2 * D_, 64, 64, 1);
  ok &= encode(enc, &prm.map[2], w2, 3, 64, F_, 8, D_ * 2, 128, 64, 64, 2);
  ok &= encode(enc, &prm.map[3], w2, 3, 64, F_, 8, D_ * 2, 128, 64, 48, 2);
  ok &= encode(enc, &prm.map[4], wo, 3, 64, D_, 8, D_ * 2, 128, 64, 64, 2);
  ok &= encode(enc, &prm.map[5], x, 2, D_, S_, 1, D_ * 2, 0, 64, 128, 1);
  ok &= encode(enc, &prm.map[6], wqkv + D_, 3, D_, D_, 2, 3 * D_ * 2, D_ * 2, 64, 64, 2);
  ok &= encode(enc, &prm.map[7], d_out, 2, D_, S_, 1, D_ * 2, 0, 64, 16, 1);
  ok &= encode(enc, &prm.map[8], d_out, 3, 64, S_, 8, D_ * 2, 128, 64, 16, 2);
  if (!ok) return;
  prm.zero = 0;
  for (int p = 0; p < 2; p++) {
    uint32_t* jb = prm.jobs + 28 * p;
    int n = 0;
    for (int c = p ? 4 : 0; c < 8; c++) {
      jb[n++] = job(B_EMPTY + 8 * slotB(c), c < 4, 8 + slotB(c), p, 1 - p, p, c, 0);
      if (c < 4) jb[n++] = job(0, 0, 8 + slotB(c), 1, 0, 1, c, 0);
    }
    for (int c = 0; c < 8; c++) jb[n++] = job(c == 3 ? B_KVFREE : B_EMPTY + 8 * slotC(c), c <= 4 && c != 3, 8 + slotC(c), p, 1 - p, 1, c, 1 + p);
    const int ms[2][8][3] = {{{2, 0, 0}, {0, 1, 2}, {5, 0, 4}, {2, 1, 6}, {0, 0, 8}, {2, 0, 11}, {-1, 0, 12}, {0, 1, 14}},
                             {{3, 0, 1}, {1, 1, 3}, {4, 1, 5}, {3, 1, 7}, {1, 0, 9}, {-1, 0, 10}, {3, 0, 13}, {1, 1, 15}}};
    for (int e = 0; e < 8; e++) jb[n++] = mjob(ms[p][e][0], ms[p][e][1], ms[p][e][2]);
  }
  fused_kernel<<<128, 384, SMEM_BYTES>>>(prm, x, wqkv, wo, w1, b1, w2, (__nv_bfloat16*)d_out);
}
```

```cpp
#include <cuda_runtime.h>
#include <cuda.h>
#include <cuda_bf16.h>
#include <stdint.h>

namespace {

constexpr int S_ = 2048, D_ = 512, F_ = 1376, FS = 176;

constexpr uint32_t SLOT = 16384;
constexpr uint32_t RING = 8 * SLOT;
constexpr uint32_t QSLOT = 24576;
constexpr uint32_t MISC = 14 * SLOT;
constexpr uint32_t B_FULL = MISC;
constexpr uint32_t B_AF = MISC + 64;
constexpr uint32_t B_EMPTY = MISC + 128;
constexpr uint32_t B_PF = MISC + 192;
constexpr uint32_t B_KVRDY = MISC + 240, B_CS2 = MISC + 248;
constexpr uint32_t B_CS1 = MISC + 256, B_OUT = MISC + 264, B_KVPART = MISC + 272, B_DONE = MISC + 280;
constexpr uint32_t EXT2 = MISC + 320, EXT1 = EXT2 + 22 * 48;
constexpr uint32_t ONES = EXT1 + 24 * 48;
constexpr uint32_t KVS = 0;
constexpr uint32_t SMEM_BYTES = 232448;

constexpr int SPIN_LIMIT = 1 << 19;

constexpr int NSUM = 576, SUM_1 = 384, SUM_2 = 480;
__device__ float4 g_sum[2 * 8 * NSUM];
__device__ float4 g_st[16 * 8 * 8];
__device__ unsigned g_flag[16 * 32];
__device__ unsigned g_epoch[128];

__device__ __forceinline__ void mbar_init(uint32_t bar, uint32_t cnt) { asm volatile("mbarrier.init.shared::cta.b64 [%0], %1;" ::"r"(bar), "r"(cnt) : "memory"); }
__device__ __forceinline__ void mbar_expect_tx(uint32_t bar, uint32_t bytes) { asm volatile("mbarrier.arrive.expect_tx.shared::cta.b64 _, [%0], %1;" ::"r"(bar), "r"(bytes) : "memory"); }
__device__ __forceinline__ void mbar_arrive(uint32_t bar) { asm volatile("mbarrier.arrive.shared::cta.b64 _, [%0];" ::"r"(bar) : "memory"); }
__device__ __forceinline__ void mbar_arrive_n(uint32_t bar, uint32_t n) { asm volatile("mbarrier.arrive.shared::cta.b64 _, [%0], %1;" ::"r"(bar), "r"(n) : "memory"); }
__device__ __forceinline__ bool mbar_try(uint32_t bar, uint32_t parity) {
  uint32_t ok;
  asm volatile("{ .reg .pred p; mbarrier.try_wait.parity.shared::cta.b64 p, [%1], %2; selp.u32 %0, 1, 0, p; }" : "=r"(ok) : "r"(bar), "r"(parity) : "memory");
  return ok;
}
__device__ __forceinline__ bool mbar_test(uint32_t bar, uint32_t parity) {
  uint32_t ok;
  asm volatile("{ .reg .pred p; mbarrier.test_wait.parity.shared::cta.b64 p, [%1], %2; selp.u32 %0, 1, 0, p; }" : "=r"(ok) : "r"(bar), "r"(parity) : "memory");
  return ok;
}
__device__ __forceinline__ bool mbar_test(uint32_t bar, uint32_t parity, float& a, float& b, uint32_t zero) {
  uint32_t ok;
  asm volatile("{ .reg .pred p; mbarrier.test_wait.parity.shared::cta.b64 p, [%3], %4; selp.u32 %0, 1, 0, p; @p add.f32 %1, %1, %5; @p add.f32 %2, %2, %5; }"
               : "=r"(ok), "+f"(a), "+f"(b) : "r"(bar), "r"(parity), "f"(__uint_as_float(zero)) : "memory");
  return ok;
}
__device__ __forceinline__ bool mbar_test(uint32_t bar, uint32_t parity, uint32_t& a, uint32_t& b, uint32_t zero) {
  uint32_t ok;
  asm volatile("{ .reg .pred p; mbarrier.test_wait.parity.shared::cta.b64 p, [%3], %4; selp.u32 %0, 1, 0, p; @p add.u32 %1, %1, %5; @p add.u32 %2, %2, %5; }"
               : "=r"(ok), "+r"(a), "+r"(b) : "r"(bar), "r"(parity), "r"(zero) : "memory");
  return ok;
}
__device__ __forceinline__ void here(float& a, float& b, uint32_t zero) {
  asm volatile("{ .reg .b32 t; mov.u32 t, %%clock; and.b32 t, t, %2; add.f32 %0, %0, t; add.f32 %1, %1, t; }" : "+f"(a), "+f"(b) : "r"(zero) : "memory");
}
__device__ __forceinline__ uint32_t after(uint32_t a, uint32_t v, uint32_t zero) {
  uint32_t r;
  asm("lop3.b32 %0, %1, %2, %3, 0xf8;" : "=r"(r) : "r"(a), "r"(v), "r"(zero));
  return r;
}
__device__ __forceinline__ void mbar_wait(uint32_t bar, uint32_t parity, uint32_t& left) {
  asm volatile("{ .reg .pred p;\n"
               "W: mbarrier.try_wait.parity.shared::cta.b64 p, [%1], %2;\n"
               "@!p sub.u32 %0, %0, 1;\n"
               "setp.gt.and.s32 p, %0, 0, !p;\n"
               "@p bra W; }" : "+r"(left) : "r"(bar), "r"(parity) : "memory");
}
__device__ __forceinline__ void tma2d(uint32_t dst, const CUtensorMap* m, int c0, int c1, uint32_t bar) {
  asm volatile("cp.async.bulk.tensor.2d.shared::cluster.global.mbarrier::complete_tx::bytes [%0], [%1, {%3, %4}], [%2];"
               ::"r"(dst), "l"(m), "r"(bar), "r"(c0), "r"(c1) : "memory");
}
__device__ __forceinline__ void tma3d(uint32_t dst, const CUtensorMap* m, int c0, int c1, int c2, uint32_t bar) {
  asm volatile("cp.async.bulk.tensor.3d.shared::cluster.global.mbarrier::complete_tx::bytes [%0], [%1, {%3, %4, %5}], [%2];"
               ::"r"(dst), "l"(m), "r"(bar), "r"(c0), "r"(c1), "r"(c2) : "memory");
}
__device__ __forceinline__ void tma2d_store(const CUtensorMap* m, int c0, int c1, uint32_t src) {
  asm volatile("cp.async.bulk.tensor.2d.global.shared::cta.tile.bulk_group [%0, {%1, %2}], [%3];" ::"l"(m), "r"(c0), "r"(c1), "r"(src) : "memory");
}
__device__ __forceinline__ void tma3d_add(const CUtensorMap* m, int c0, int c1, int c2, uint32_t src) {
  asm volatile("cp.reduce.async.bulk.tensor.3d.global.shared::cta.add.tile.bulk_group [%0, {%1, %2, %3}], [%4];" ::"l"(m), "r"(c0), "r"(c1), "r"(c2), "r"(src) : "memory");
}
__device__ __forceinline__ void tma2d_pair(uint32_t dst, const CUtensorMap* m, int c0, int c1, uint32_t bar) {
  asm volatile("cp.async.bulk.tensor.2d.shared::cluster.global.mbarrier::complete_tx::bytes.multicast::cluster [%0], [%1, {%3, %4}], [%2], %5;"
               ::"r"(dst), "l"(m), "r"(bar), "r"(c0), "r"(c1), "h"((uint16_t)3) : "memory");
}
__device__ __forceinline__ void p1_load_w(uint32_t live, uint32_t bar, uint32_t dst, const CUtensorMap* m, int c0, int c1, const CUtensorMap* mf, int cf) {
  asm volatile("{ .reg .pred p; .reg .b32 d; setp.ne.u32 p, %0, 0; add.u32 d, %2, 16384;\n"
               "@p mbarrier.arrive.expect_tx.shared::cta.b64 _, [%1], 40960;\n"
               "@p cp.async.bulk.tensor.3d.shared::cluster.global.mbarrier::complete_tx::bytes [%2], [%3, {%4, %5, %6}], [%1];\n"
               "@p cp.async.bulk.tensor.2d.shared::cluster.global.mbarrier::complete_tx::bytes [d], [%7, {%8, %5}], [%1]; }"
               ::"r"(live), "r"(bar), "r"(dst), "l"(m), "r"(c0), "r"(c1), "r"(0), "l"(mf), "r"(cf) : "memory");
}
__device__ __forceinline__ void p1_load_elect(uint32_t bar, uint32_t dx, const CUtensorMap* mx, int cx, int rx, uint32_t dw, const CUtensorMap* mw, int cw,
                                              const CUtensorMap* mf, int cf) {
  asm volatile("{ .reg .pred p; .reg .b32 d; elect.sync _|p, 0xffffffff; add.u32 d, %5, 16384;\n"
               "@p mbarrier.arrive.expect_tx.shared::cta.b64 _, [%0], 40960;\n"
               "@p cp.async.bulk.tensor.2d.shared::cluster.global.mbarrier::complete_tx::bytes [%1], [%2, {%3, %4}], [%0];\n"
               "@p cp.async.bulk.tensor.3d.shared::cluster.global.mbarrier::complete_tx::bytes [%5], [%6, {%7, %3, %8}], [%0];\n"
               "@p cp.async.bulk.tensor.2d.shared::cluster.global.mbarrier::complete_tx::bytes [d], [%9, {%10, %3}], [%0]; }"
               ::"r"(bar), "r"(dx), "l"(mx), "r"(cx), "r"(rx), "r"(dw), "l"(mw), "r"(cw), "r"(0), "l"(mf), "r"(cf) : "memory");
}
__device__ __forceinline__ void tma2d_add_elect(const CUtensorMap* m, int c0, int c1, uint32_t src) {
  asm volatile("{ .reg .pred p; elect.sync _|p, 0xffffffff;\n"
               "@p cp.reduce.async.bulk.tensor.2d.global.shared::cta.add.tile.bulk_group [%0, {%1, %2}], [%3];\n"
               "@p cp.async.bulk.commit_group; }" ::"l"(m), "r"(c0), "r"(c1), "r"(src) : "memory");
}
__device__ __forceinline__ void tma3d_add_elect(const CUtensorMap* m, int c0, int c1, int c2, uint32_t src) {
  asm volatile("{ .reg .pred p; elect.sync _|p, 0xffffffff;\n"
               "@p cp.reduce.async.bulk.tensor.3d.global.shared::cta.add.tile.bulk_group [%0, {%1, %2, %3}], [%4];\n"
               "@p cp.async.bulk.commit_group; }" ::"l"(m), "r"(c0), "r"(c1), "r"(c2), "r"(src) : "memory");
}
__device__ __forceinline__ void bulk_peer_elect(uint32_t dst, uint32_t src, uint32_t bytes, uint32_t bar) {
  asm volatile("{ .reg .pred p; elect.sync _|p, 0xffffffff;\n"
               "@p cp.async.bulk.shared::cluster.shared::cta.mbarrier::complete_tx::bytes [%0], [%1], %2, [%3]; }" ::"r"(dst), "r"(src), "r"(bytes), "r"(bar) : "memory");
}
__device__ __forceinline__ void bulk_commit() { asm volatile("cp.async.bulk.commit_group;" ::: "memory"); }
template <int N> __device__ __forceinline__ void bulk_wait_read() { asm volatile("cp.async.bulk.wait_group.read %0;" ::"n"(N) : "memory"); }
__device__ __forceinline__ void bulk_wait() { asm volatile("cp.async.bulk.wait_group 0;" ::: "memory"); }
__device__ __forceinline__ void bulk_peer(uint32_t dst, uint32_t src, uint32_t bytes, uint32_t bar) {
  asm volatile("cp.async.bulk.shared::cluster.shared::cta.mbarrier::complete_tx::bytes [%0], [%1], %2, [%3];" ::"r"(dst), "r"(src), "r"(bytes), "r"(bar) : "memory");
}
__device__ __forceinline__ void mbar_arrive_peer(uint32_t bar) { asm volatile("mbarrier.arrive.shared::cluster.b64 _, [%0];" ::"r"(bar) : "memory"); }
__device__ __forceinline__ uint32_t mapa(uint32_t a, uint32_t cta) { uint32_t r; asm("mapa.shared::cluster.u32 %0, %1, %2;" : "=r"(r) : "r"(a), "r"(cta)); return r; }
__device__ __forceinline__ void prefetch_map(const CUtensorMap* m) { asm volatile("prefetch.tensormap [%0];" ::"l"(m) : "memory"); }
__device__ __forceinline__ void prefetch_l2(const void* p, uint32_t bytes) { asm volatile("cp.async.bulk.prefetch.L2.global [%0], %1;" ::"l"(p), "r"(bytes) : "memory"); }
__device__ __forceinline__ void wg_fence() { asm volatile("wgmma.fence.sync.aligned;" ::: "memory"); }
__device__ __forceinline__ void wg_commit() { asm volatile("wgmma.commit_group.sync.aligned;" ::: "memory"); }
template <int N> __device__ __forceinline__ void wg_wait() { asm volatile("wgmma.wait_group.sync.aligned %0;" ::"n"(N) : "memory"); }
template <int O, int N, int SZ> __device__ __forceinline__ void reg_fence(float (&d)[SZ]) {
#pragma unroll
  for (int k = 0; k < N; k++) asm volatile("" : "+f"(d[O + k])::"memory");
}
__device__ __forceinline__ void fence_async() { asm volatile("fence.proxy.async.shared::cta;" ::: "memory"); }
__device__ __forceinline__ void fence_async_all() { asm volatile("fence.proxy.async;" ::: "memory"); }
__device__ __forceinline__ void bar_wg(int id) { asm volatile("bar.sync %0, 128;" ::"r"(id) : "memory"); }
__device__ __forceinline__ uint32_t pack(float lo, float hi) { uint32_t r; asm("cvt.rn.bf16x2.f32 %0, %1, %2;" : "=r"(r) : "f"(hi), "f"(lo)); return r; }
__device__ __forceinline__ float bflo(uint32_t w) { return __uint_as_float(w << 16); }
__device__ __forceinline__ float bfhi(uint32_t w) { return __uint_as_float(w & 0xffff0000u); }
__device__ __forceinline__ float ex2(float x) { float r; asm("ex2.approx.ftz.f32 %0, %1;" : "=f"(r) : "f"(x)); return r; }
__device__ __forceinline__ float sqrt_(float x) { float r; asm("sqrt.approx.ftz.f32 %0, %1;" : "=f"(r) : "f"(x)); return r; }
__device__ __forceinline__ float rcp(float x) { float r; asm("rcp.approx.ftz.f32 %0, %1;" : "=f"(r) : "f"(x)); return r; }
__device__ __forceinline__ uint4 lds128(uint32_t a) { uint4 v; asm volatile("ld.shared.v4.u32 {%0,%1,%2,%3}, [%4];" : "=r"(v.x), "=r"(v.y), "=r"(v.z), "=r"(v.w) : "r"(a) : "memory"); return v; }
__device__ __forceinline__ float4 lds128f(uint32_t a) { float4 v; asm volatile("ld.shared.v4.f32 {%0,%1,%2,%3}, [%4];" : "=f"(v.x), "=f"(v.y), "=f"(v.z), "=f"(v.w) : "r"(a) : "memory"); return v; }
__device__ __forceinline__ float2 lds64f(uint32_t a) { float2 v; asm volatile("ld.shared.v2.f32 {%0,%1}, [%2];" : "=f"(v.x), "=f"(v.y) : "r"(a) : "memory"); return v; }
__device__ __forceinline__ uint32_t lds32(uint32_t a) { uint32_t v; asm volatile("ld.shared.u32 %0, [%1];" : "=r"(v) : "r"(a) : "memory"); return v; }
__device__ __forceinline__ void sts128(uint32_t a, uint32_t x, uint32_t y, uint32_t z, uint32_t w) { asm volatile("st.shared.v4.u32 [%0], {%1,%2,%3,%4};" ::"r"(a), "r"(x), "r"(y), "r"(z), "r"(w) : "memory"); }
__device__ __forceinline__ void sts128f(uint32_t a, float x, float y, float z, float w) { asm volatile("st.shared.v4.f32 [%0], {%1,%2,%3,%4};" ::"r"(a), "f"(x), "f"(y), "f"(z), "f"(w) : "memory"); }
__device__ __forceinline__ void sts64(uint32_t a, uint32_t x, uint32_t y) { asm volatile("st.shared.v2.u32 [%0], {%1,%2};" ::"r"(a), "r"(x), "r"(y) : "memory"); }
__device__ __forceinline__ void sts32f(uint32_t a, float x) { asm volatile("st.shared.f32 [%0], %1;" ::"r"(a), "f"(x) : "memory"); }
__device__ __forceinline__ void stsm4(uint32_t a, uint32_t r0, uint32_t r1, uint32_t r2, uint32_t r3) {
  asm volatile("stmatrix.sync.aligned.m8n8.x4.shared.b16 [%0], {%1,%2,%3,%4};" ::"r"(a), "r"(r0), "r"(r1), "r"(r2), "r"(r3) : "memory");
}
__device__ __forceinline__ void mma16816(float (&d)[4], uint32_t a0, uint32_t a1, uint32_t a2, uint32_t a3, uint32_t b0, uint32_t b1) {
  asm volatile("mma.sync.aligned.m16n8k16.row.col.f32.bf16.bf16.f32 {%0,%1,%2,%3}, {%4,%5,%6,%7}, {%8,%9}, {%0,%1,%2,%3};"
               : "+f"(d[0]), "+f"(d[1]), "+f"(d[2]), "+f"(d[3]) : "r"(a0), "r"(a1), "r"(a2), "r"(a3), "r"(b0), "r"(b1));
}
__device__ __forceinline__ uint32_t sub_bf2(uint32_t a, uint32_t b) { uint32_t r; asm("sub.rn.bf16x2 %0, %1, %2;" : "=r"(r) : "r"(a), "r"(b)); return r; }
__device__ __forceinline__ void ldsm4(uint32_t a, uint32_t* r) {
  asm volatile("ldmatrix.sync.aligned.m8n8.x4.shared.b16 {%0,%1,%2,%3}, [%4];" : "=r"(r[0]), "=r"(r[1]), "=r"(r[2]), "=r"(r[3]) : "r"(a) : "memory");
}
__device__ __forceinline__ uint4 ldg_nc128(const void* p) { uint4 v; asm volatile("ld.global.nc.L1::no_allocate.v4.u32 {%0,%1,%2,%3}, [%4];" : "=r"(v.x), "=r"(v.y), "=r"(v.z), "=r"(v.w) : "l"(p)); return v; }
__device__ __forceinline__ uint32_t ldg_nc32(const void* p) { uint32_t v; asm volatile("ld.global.nc.u32 %0, [%1];" : "=r"(v) : "l"(p)); return v; }
__device__ __forceinline__ float4 ld_rlx128f(const void* p) { float4 v; asm volatile("ld.relaxed.gpu.global.v4.f32 {%0,%1,%2,%3}, [%4];" : "=f"(v.x), "=f"(v.y), "=f"(v.z), "=f"(v.w) : "l"(p) : "memory"); return v; }
__device__ __forceinline__ void red128f(float4* p, float x, float y, float z, float w) { asm volatile("red.relaxed.gpu.global.add.v4.f32 [%0], {%1,%2,%3,%4};" ::"l"(p), "f"(x), "f"(y), "f"(z), "f"(w) : "memory"); }
__device__ __forceinline__ uint64_t ld_rlx64(const uint64_t* p) { uint64_t v; asm volatile("ld.relaxed.gpu.global.b64 %0, [%1];" : "=l"(v) : "l"(p) : "memory"); return v; }
__device__ __forceinline__ void ld_rlx2x64(const uint64_t* p, uint64_t& a, uint64_t& b) { asm volatile("ld.relaxed.gpu.global.v2.b64 {%0,%1}, [%2];" : "=l"(a), "=l"(b) : "l"(p) : "memory"); }
__device__ __forceinline__ void st_rlx128(void* p, uint32_t x, uint32_t y, uint32_t z, uint32_t w) { asm volatile("st.relaxed.gpu.global.v4.u32 [%0], {%1,%2,%3,%4};" ::"l"(p), "r"(x), "r"(y), "r"(z), "r"(w) : "memory"); }
__device__ __forceinline__ void st_rlx64(void* p, uint32_t x, uint32_t y) { asm volatile("st.relaxed.gpu.global.v2.u32 [%0], {%1,%2};" ::"l"(p), "r"(x), "r"(y) : "memory"); }
__device__ __forceinline__ uint2 lds64(uint32_t a) { uint2 v; asm volatile("ld.shared.v2.u32 {%0,%1}, [%2];" : "=r"(v.x), "=r"(v.y) : "r"(a) : "memory"); return v; }
__device__ __forceinline__ void st_rlx64(uint64_t* p, uint64_t v) { asm volatile("st.relaxed.gpu.global.b64 [%0], %1;" ::"l"(p), "l"(v) : "memory"); }
__device__ __forceinline__ uint32_t ld_rlx32(const unsigned* p) { uint32_t v; asm volatile("ld.relaxed.gpu.global.u32 %0, [%1];" : "=r"(v) : "l"(p) : "memory"); return v; }
__device__ __forceinline__ void st_rlx32(void* p, uint32_t v) { asm volatile("st.relaxed.gpu.global.u32 [%0], %1;" ::"l"(p), "r"(v) : "memory"); }
__device__ __forceinline__ void sts32(uint32_t a, uint32_t x) { asm volatile("st.shared.u32 [%0], %1;" ::"r"(a), "r"(x) : "memory"); }
__device__ __forceinline__ void sts16(uint32_t a, uint32_t x) { asm volatile("{ .reg .b16 h; cvt.u16.u32 h, %1; st.shared.u16 [%0], h; }" ::"r"(a), "r"(x) : "memory"); }
__device__ __forceinline__ uint2 ldg_nc64(const void* p) { uint2 v; asm volatile("ld.global.nc.v2.u32 {%0,%1}, [%2];" : "=r"(v.x), "=r"(v.y) : "l"(p)); return v; }
__device__ __forceinline__ float add_sat(float a, float b) { float r; asm("add.sat.f32 %0, %1, %2;" : "=f"(r) : "f"(a), "f"(b)); return r; }
__device__ __forceinline__ float2 ldc64f(uint32_t a) { float2 v; asm("ld.shared.v2.f32 {%0,%1}, [%2];" : "=f"(v.x), "=f"(v.y) : "r"(a)); return v; }
__device__ __forceinline__ float4 ldc128f(uint32_t a) { float4 v; asm("ld.shared.v4.f32 {%0,%1,%2,%3}, [%4];" : "=f"(v.x), "=f"(v.y), "=f"(v.z), "=f"(v.w) : "r"(a)); return v; }
__device__ __forceinline__ void pin(uint32_t& a) { asm volatile("" : "+r"(a)::"memory"); }
__device__ __forceinline__ void pin2(uint32_t zero, uint32_t a, uint32_t b) {
  asm volatile("{ .reg .pred p; setp.ne.u32 p, %0, 0; @p st.shared.v2.u32 [%0], {%1, %2}; }" ::"r"(zero), "r"(a), "r"(b) : "memory");
}
__device__ __forceinline__ void pin4(uint32_t zero, const float* a) {
  asm volatile("{ .reg .pred p; setp.ne.u32 p, %0, 0; @p st.shared.v4.f32 [%0], {%1, %2, %3, %4}; }" ::"r"(zero), "f"(a[0]), "f"(a[1]), "f"(a[2]), "f"(a[3]) : "memory");
}
constexpr uint32_t HI_SW = (1024 >> 4) | (1u << 30);
constexpr uint32_t HI_NS = 256 >> 4;
constexpr uint32_t HI_EX = 48 >> 4;
#define R8(d, o) "+f"(d[(o)]), "+f"(d[(o) + 1]), "+f"(d[(o) + 2]), "+f"(d[(o) + 3]), "+f"(d[(o) + 4]), "+f"(d[(o) + 5]), "+f"(d[(o) + 6]), "+f"(d[(o) + 7])
template <int O, int SC, uint32_t HA = HI_SW, uint32_t HB = HI_SW, int SZ>
__device__ __forceinline__ void wg192_ss(float (&d)[SZ], uint32_t da, uint32_t db) {
  asm volatile("{ .reg .pred p; .reg .b32 h, k; .reg .b64 a, b; setp.ne.b32 p, %98, 0; mov.b32 h, %99; mov.b32 k, %100; mov.b64 a, {%96, h}; mov.b64 b, {%97, k};\n"
    "wgmma.mma_async.sync.aligned.m64n192k16.f32.bf16.bf16 {%0,%1,%2,%3,%4,%5,%6,%7,%8,%9,%10,%11,%12,%13,%14,%15,%16,%17,%18,%19,%20,%21,%22,%23,%24,%25,%26,%27,%28,%29,%30,%31,%32,%33,%34,%35,%36,%37,%38,%39,%40,%41,%42,%43,%44,%45,%46,%47,%48,%49,%50,%51,%52,%53,%54,%55,%56,%57,%58,%59,%60,%61,%62,%63,%64,%65,%66,%67,%68,%69,%70,%71,%72,%73,%74,%75,%76,%77,%78,%79,%80,%81,%82,%83,%84,%85,%86,%87,%88,%89,%90,%91,%92,%93,%94,%95}, a, b, p, 1, 1, 0, 1; }"
    : R8(d, O + 0), R8(d, O + 8), R8(d, O + 16), R8(d, O + 24), R8(d, O + 32), R8(d, O + 40), R8(d, O + 48), R8(d, O + 56), R8(d, O + 64), R8(d, O + 72), R8(d, O + 80), R8(d, O + 88) : "r"(da), "r"(db), "n"(SC), "n"(HA), "n"(HB));
}

template <int O, int SC, uint32_t HA = HI_SW, uint32_t HB = HI_SW, int SZ>
__device__ __forceinline__ void wg176_ss(float (&d)[SZ], uint32_t da, uint32_t db) {
  asm volatile("{ .reg .pred p; .reg .b32 h, k; .reg .b64 a, b; setp.ne.b32 p, %90, 0; mov.b32 h, %91; mov.b32 k, %92; mov.b64 a, {%88, h}; mov.b64 b, {%89, k};\n"
    "wgmma.mma_async.sync.aligned.m64n176k16.f32.bf16.bf16 {%0,%1,%2,%3,%4,%5,%6,%7,%8,%9,%10,%11,%12,%13,%14,%15,%16,%17,%18,%19,%20,%21,%22,%23,%24,%25,%26,%27,%28,%29,%30,%31,%32,%33,%34,%35,%36,%37,%38,%39,%40,%41,%42,%43,%44,%45,%46,%47,%48,%49,%50,%51,%52,%53,%54,%55,%56,%57,%58,%59,%60,%61,%62,%63,%64,%65,%66,%67,%68,%69,%70,%71,%72,%73,%74,%75,%76,%77,%78,%79,%80,%81,%82,%83,%84,%85,%86,%87}, a, b, p, 1, 1, 0, 1; }"
    : R8(d, O + 0), R8(d, O + 8), R8(d, O + 16), R8(d, O + 24), R8(d, O + 32), R8(d, O + 40), R8(d, O + 48), R8(d, O + 56), R8(d, O + 64), R8(d, O + 72), R8(d, O + 80) : "r"(da), "r"(db), "n"(SC), "n"(HA), "n"(HB));
}

template <int O, int SC, uint32_t HA = HI_SW, uint32_t HB = HI_SW, int SZ>
__device__ __forceinline__ void wg128_ss(float (&d)[SZ], uint32_t da, uint32_t db) {
  asm volatile("{ .reg .pred p; .reg .b32 h, k; .reg .b64 a, b; setp.ne.b32 p, %66, 0; mov.b32 h, %67; mov.b32 k, %68; mov.b64 a, {%64, h}; mov.b64 b, {%65, k};\n"
    "wgmma.mma_async.sync.aligned.m64n128k16.f32.bf16.bf16 {%0,%1,%2,%3,%4,%5,%6,%7,%8,%9,%10,%11,%12,%13,%14,%15,%16,%17,%18,%19,%20,%21,%22,%23,%24,%25,%26,%27,%28,%29,%30,%31,%32,%33,%34,%35,%36,%37,%38,%39,%40,%41,%42,%43,%44,%45,%46,%47,%48,%49,%50,%51,%52,%53,%54,%55,%56,%57,%58,%59,%60,%61,%62,%63}, a, b, p, 1, 1, 0, 1; }"
    : R8(d, O + 0), R8(d, O + 8), R8(d, O + 16), R8(d, O + 24), R8(d, O + 32), R8(d, O + 40), R8(d, O + 48), R8(d, O + 56) : "r"(da), "r"(db), "n"(SC), "n"(HA), "n"(HB));
}

template <int O, int SC, uint32_t HA = HI_SW, uint32_t HB = HI_SW, int SZ>
__device__ __forceinline__ void wg64_ss_tt(float (&d)[SZ], uint32_t da, uint32_t db) {
  asm volatile("{ .reg .pred p; .reg .b32 h, k; .reg .b64 a, b; setp.ne.b32 p, %34, 0; mov.b32 h, %35; mov.b32 k, %36; mov.b64 a, {%32, h}; mov.b64 b, {%33, k};\n"
    "wgmma.mma_async.sync.aligned.m64n64k16.f32.bf16.bf16 {%0,%1,%2,%3,%4,%5,%6,%7,%8,%9,%10,%11,%12,%13,%14,%15,%16,%17,%18,%19,%20,%21,%22,%23,%24,%25,%26,%27,%28,%29,%30,%31}, a, b, p, 1, 1, 1, 1; }"
    : R8(d, O + 0), R8(d, O + 8), R8(d, O + 16), R8(d, O + 24) : "r"(da), "r"(db), "n"(SC), "n"(HA), "n"(HB));
}

template <int O, int SC, uint32_t HA = HI_SW, uint32_t HB = HI_SW, int SZ>
__device__ __forceinline__ void wg8_ss_tn(float (&d)[SZ], uint32_t da, uint32_t db) {
  asm volatile("{ .reg .pred p; .reg .b32 h, k; .reg .b64 a, b; setp.ne.b32 p, %6, 0; mov.b32 h, %7; mov.b32 k, %8; mov.b64 a, {%4, h}; mov.b64 b, {%5, k};\n"
    "wgmma.mma_async.sync.aligned.m64n8k16.f32.bf16.bf16 {%0,%1,%2,%3}, a, b, p, 1, 1, 1, 0; }"
    : "+f"(d[O + 0]), "+f"(d[O + 1]), "+f"(d[O + 2]), "+f"(d[O + 3]) : "r"(da), "r"(db), "n"(SC), "n"(HA), "n"(HB));
}

template <int O, int SC, uint32_t HB, int SZ>
__device__ __forceinline__ void wg192_rs(float (&d)[SZ], uint32_t a0, uint32_t a1, uint32_t a2, uint32_t a3, uint32_t db) {
  asm volatile("{ .reg .pred p; .reg .b32 k; .reg .b64 b; setp.ne.b32 p, %101, 0; mov.b32 k, %102; mov.b64 b, {%100, k};\n"
    "wgmma.mma_async.sync.aligned.m64n192k16.f32.bf16.bf16 {%0,%1,%2,%3,%4,%5,%6,%7,%8,%9,%10,%11,%12,%13,%14,%15,%16,%17,%18,%19,%20,%21,%22,%23,%24,%25,%26,%27,%28,%29,%30,%31,%32,%33,%34,%35,%36,%37,%38,%39,%40,%41,%42,%43,%44,%45,%46,%47,%48,%49,%50,%51,%52,%53,%54,%55,%56,%57,%58,%59,%60,%61,%62,%63,%64,%65,%66,%67,%68,%69,%70,%71,%72,%73,%74,%75,%76,%77,%78,%79,%80,%81,%82,%83,%84,%85,%86,%87,%88,%89,%90,%91,%92,%93,%94,%95}, {%96,%97,%98,%99}, b, p, 1, 1, 1; }"
    : R8(d, O + 0), R8(d, O + 8), R8(d, O + 16), R8(d, O + 24), R8(d, O + 32), R8(d, O + 40), R8(d, O + 48), R8(d, O + 56), R8(d, O + 64), R8(d, O + 72), R8(d, O + 80), R8(d, O + 88) : "r"(a0), "r"(a1), "r"(a2), "r"(a3), "r"(db), "n"(SC), "n"(HB));
}

template <int O, int SC, uint32_t HB, int SZ>
__device__ __forceinline__ void wg176_rs(float (&d)[SZ], uint32_t a0, uint32_t a1, uint32_t a2, uint32_t a3, uint32_t db) {
  asm volatile("{ .reg .pred p; .reg .b32 k; .reg .b64 b; setp.ne.b32 p, %93, 0; mov.b32 k, %94; mov.b64 b, {%92, k};\n"
    "wgmma.mma_async.sync.aligned.m64n176k16.f32.bf16.bf16 {%0,%1,%2,%3,%4,%5,%6,%7,%8,%9,%10,%11,%12,%13,%14,%15,%16,%17,%18,%19,%20,%21,%22,%23,%24,%25,%26,%27,%28,%29,%30,%31,%32,%33,%34,%35,%36,%37,%38,%39,%40,%41,%42,%43,%44,%45,%46,%47,%48,%49,%50,%51,%52,%53,%54,%55,%56,%57,%58,%59,%60,%61,%62,%63,%64,%65,%66,%67,%68,%69,%70,%71,%72,%73,%74,%75,%76,%77,%78,%79,%80,%81,%82,%83,%84,%85,%86,%87}, {%88,%89,%90,%91}, b, p, 1, 1, 1; }"
    : R8(d, O + 0), R8(d, O + 8), R8(d, O + 16), R8(d, O + 24), R8(d, O + 32), R8(d, O + 40), R8(d, O + 48), R8(d, O + 56), R8(d, O + 64), R8(d, O + 72), R8(d, O + 80) : "r"(a0), "r"(a1), "r"(a2), "r"(a3), "r"(db), "n"(SC), "n"(HB));
}

template <int O, int SC, uint32_t HB, int SZ>
__device__ __forceinline__ void wg128_rs(float (&d)[SZ], uint32_t a0, uint32_t a1, uint32_t a2, uint32_t a3, uint32_t db) {
  asm volatile("{ .reg .pred p; .reg .b32 k; .reg .b64 b; setp.ne.b32 p, %69, 0; mov.b32 k, %70; mov.b64 b, {%68, k};\n"
    "wgmma.mma_async.sync.aligned.m64n128k16.f32.bf16.bf16 {%0,%1,%2,%3,%4,%5,%6,%7,%8,%9,%10,%11,%12,%13,%14,%15,%16,%17,%18,%19,%20,%21,%22,%23,%24,%25,%26,%27,%28,%29,%30,%31,%32,%33,%34,%35,%36,%37,%38,%39,%40,%41,%42,%43,%44,%45,%46,%47,%48,%49,%50,%51,%52,%53,%54,%55,%56,%57,%58,%59,%60,%61,%62,%63}, {%64,%65,%66,%67}, b, p, 1, 1, 1; }"
    : R8(d, O + 0), R8(d, O + 8), R8(d, O + 16), R8(d, O + 24), R8(d, O + 32), R8(d, O + 40), R8(d, O + 48), R8(d, O + 56) : "r"(a0), "r"(a1), "r"(a2), "r"(a3), "r"(db), "n"(SC), "n"(HB));
}

template <int O, int SC, uint32_t HB, int SZ>
__device__ __forceinline__ void wg24_rs(float (&d)[SZ], uint32_t a0, uint32_t a1, uint32_t a2, uint32_t a3, uint32_t db) {
  asm volatile("{ .reg .pred p; .reg .b32 k; .reg .b64 b; setp.ne.b32 p, %17, 0; mov.b32 k, %18; mov.b64 b, {%16, k};\n"
    "wgmma.mma_async.sync.aligned.m64n24k16.f32.bf16.bf16 {%0,%1,%2,%3,%4,%5,%6,%7,%8,%9,%10,%11}, {%12,%13,%14,%15}, b, p, 1, 1, 0; }"
    : R8(d, O + 0), "+f"(d[O + 8]), "+f"(d[O + 9]), "+f"(d[O + 10]), "+f"(d[O + 11]) : "r"(a0), "r"(a1), "r"(a2), "r"(a3), "r"(db), "n"(SC), "n"(HB));
}

template <int V> struct IC { static constexpr int v = V; };
template <int I, int N, class Fn> __device__ __forceinline__ void sfor(Fn&& f) {
  if constexpr (I < N) { f(IC<I>{}); sfor<I + 1, N>(f); }
}
#define LAM(X) [&](auto X) __attribute__((always_inline))
#define INL __attribute__((always_inline))

__host__ __device__ constexpr uint32_t LBO(uint32_t b) { return (b >> 4) << 16; }
constexpr float LOG2E = 1.4426950408889634f, LN2 = 0.6931471805599453f;
#define CREGS 216
#define PREGS 72
#define STR_(x) #x
#define STR(x) STR_(x)
#define CSWAIT 0
#define QFWAIT 4
#define ST1 3
#define GC 5
#define PINH 1
#define LGL 2
#define LG0 16
#define EW 8
#define XL 0
#define A0 3
#define RSM 0x1e4
#define MC 1
#define XWIN P1WIN
#define HERE 1
#define PP0 40
#define PP1 31
#define P1WIN 2

__host__ __device__ constexpr uint32_t full(int n) { return B_FULL + 8 * (n & 7); }
__host__ __device__ constexpr uint32_t empty(int n) { return B_EMPTY + 8 * (n & 7); }
__host__ __device__ constexpr int par(int n) { return (n >> 3) & 1; }
__host__ __device__ constexpr int tileS(int s) { return (0xf158 >> s) & 1; }
__host__ __device__ constexpr int partS(int s) { return (int)((0x3211321332200100ull >> (4 * s)) & 15); }
__host__ __device__ constexpr int peerS(int s) { return (0xee12 >> s) & 1; }
__host__ __device__ constexpr int slotA(int part, int peer) { return ((peer ? 0x3753 : 0x1642) >> (4 * part)) & 15; }

struct alignas(64) Params {
  CUtensorMap map[8];
  uint32_t zero;
  uint32_t jobs[16];
};

#define TS(role, k)
#define TSG(role, k)

__device__ __forceinline__ float phi(float u, float rs, float rl) {
  return fmaxf(add_sat(ex2(u * rl), 1e-6f), fmaf(u, rs, 1.000001f));
}
template <bool SCALED> __device__ __forceinline__ float mish(float u, float rs, float rl) {
  const float v = ex2(SCALED ? fmaf(u, LOG2E, rl) : fmaf(u, rl, -0.5f)), h = SCALED ? u : u * rs;
  return fmaf(-h, rcp(fmaf(v, v + 1.41421356237f, 1.f)), h);
}
__device__ __forceinline__ uint32_t split(float& v) { const uint32_t h = pack(v, 0.f); v -= bflo(h); return h; }

__device__ __forceinline__ bool fresh(const float4& a, uint32_t tag) {
  return !(((__float_as_uint(a.x) ^ tag) | (__float_as_uint(a.y) ^ tag) | (__float_as_uint(a.z) ^ tag) | (__float_as_uint(a.w) ^ tag)) & 1);
}
__device__ __forceinline__ uint32_t kvpart(int h, int lane) { return SLOT + (lane >> 1) * 128 + (((2 * h + (lane & 1)) ^ ((lane >> 1) & 7)) << 4); }
__device__ __forceinline__ void add8(float (&s)[8], const uint4& v) {
  s[0] += bflo(v.x); s[1] += bfhi(v.x); s[2] += bflo(v.y); s[3] += bfhi(v.y);
  s[4] += bflo(v.z); s[5] += bfhi(v.z); s[6] += bflo(v.w); s[7] += bfhi(v.w);
}

__global__ void __cluster_dims__(2, 1, 1) __launch_bounds__(384, 1)
fused_kernel(const __grid_constant__ Params prm, const __nv_bfloat16* __restrict__ x, const __nv_bfloat16* __restrict__ wqkv,
             const __nv_bfloat16* __restrict__ wo, const __nv_bfloat16* __restrict__ w1, const __nv_bfloat16* __restrict__ b1,
             const __nv_bfloat16* __restrict__ w2, __nv_bfloat16* __restrict__ out) {
  extern __shared__ __align__(1024) uint8_t smem_raw[];
  const uint32_t sb = __reduce_max_sync(0xffffffffu, (uint32_t)__cvta_generic_to_shared(smem_raw));
  const int i = blockIdx.x >> 3, j = blockIdx.x & 7;
  const int warp = __reduce_max_sync(0xffffffffu, threadIdx.x >> 5);
  const int lane = threadIdx.x & 31;
  uint32_t left = 1u << 16;

  TS(threadIdx.x >> 7, 0);
  TSG(threadIdx.x >> 7, 62);
  if (warp == 8) {
    if (lane == 0) {
#pragma unroll
      for (int c = 0; c < P1WIN; c++) mbar_init(sb + B_FULL + 8 * c, 1);
      asm volatile("fence.mbarrier_init.release.cluster;" ::: "memory");
    }
    __syncwarp();
#pragma unroll
    for (int c = 0; c < P1WIN; c++) p1_load_elect(sb + B_FULL + 8 * c, sb + c * SLOT, &prm.map[5], 64 * c, 128 * i, sb + RING + c * QSLOT, &prm.map[6], 64 * j, &prm.map[1], FS * j);
    TS(2, 44);
  } else if (warp < 8) {
    if (lane == 0) {
      if (warp >= P1WIN) mbar_init(sb + MISC + 8 * warp, 1);
#pragma unroll
      for (int k = 1; k < 4; k++) mbar_init(sb + MISC + 64 * k + 8 * warp, k == 1 ? 1 : (k == 2 ? 8 : 4));
      if (warp < 4) mbar_init(sb + MISC + 256 + 8 * warp, warp < 2 ? 1 : 8);
      asm volatile("fence.mbarrier_init.release.cluster;" ::: "memory");
    }
  } else if (warp == 9) {
    if (lane < 16) sts128(sb + ONES + lane * 16, 0x3f803f80u, 0x3f803f80u, 0x3f803f80u, 0x3f803f80u);
  }
  TS(threadIdx.x >> 7, 41);
  __syncthreads();
  asm volatile("barrier.cluster.arrive.relaxed.aligned;" ::: "memory");
  TS(threadIdx.x >> 7, 42);

  if (warp >= 8) {
    asm volatile("setmaxnreg.dec.sync.aligned.u32 " STR(PREGS) ";");
    auto gather = [&](const float4* p, bool on, int lanes, const __nv_bfloat16* bias, uint32_t dst) INL {
      const uint4 bv = bias ? ldg_nc128(bias) : make_uint4(0, 0, 0, 0);
      float4 a, b, c;
      int it = 0;
      while (true) {
        a = ld_rlx128f(p); b = ld_rlx128f(p + 32); c = ld_rlx128f(p + 64);
        if (__all_sync(0xffffffffu, !on || (a.w == 32.f && b.w == 32.f && c.w == 32.f)) || ++it > SPIN_LIMIT) break;
        __nanosleep(32);
      }
      const float v[8] = {a.x, a.y, a.z, b.x, b.y, b.z, c.x, c.y};
      uint32_t h[4], r[4];
#pragma unroll
      for (int k = 0; k < 4; k++) { h[k] = pack(v[2 * k], v[2 * k + 1]); r[k] = pack(v[2 * k] - bflo(h[k]), v[2 * k + 1] - bfhi(h[k])); }
      if (lane < lanes) {
        sts128(dst + 48 * lane, h[0], h[1], h[2], h[3]);
        sts128(dst + 48 * lane + 16, r[0], r[1], r[2], r[3]);
        sts128(dst + 48 * lane + 32, bv.x, bv.y, bv.z, bv.w);
      }
      fence_async();
      __syncwarp();
    };
    if (warp <= 9) {
      if (warp == 9) {
        if (lane == 0) {
#pragma unroll
          for (int k = 0; k < 8; k++) mbar_expect_tx(sb + B_AF + 8 * k, 8192);
#pragma unroll
          for (int k = 0; k < 5; k++) if (k != 1) prefetch_map(&prm.map[k]);
        }
        const float4* const sum = &g_sum[((ld_rlx32(&g_epoch[blockIdx.x]) & 1) * 8 + j) * NSUM];
#pragma unroll 1
        for (int c = 0; c < 8; c++) {
          mbar_wait(sb + B_FULL + 8 * c, 0, left);
          if (lane == 0 && c < 8 - P1WIN) tma2d(sb + (c + P1WIN) * SLOT, &prm.map[5], 64 * (c + P1WIN), 128 * i, sb + B_FULL + 8 * (c + P1WIN));
          if (lane == 0) { tma2d_store(&prm.map[7], 64 * c, 128 * i + 16 * j, sb + c * SLOT + 2048 * j); bulk_commit(); }
          if (c == GC) {
            gather(sum + SUM_1 + lane, lane < 24, 24, (lane >> 3) == 2 ? b1 + FS * j + 8 * (lane - 16) : nullptr, sb + EXT1);
            if (lane == 0) { bulk_wait_read<GC - 3>(); mbar_arrive(sb + B_CS1); }
            TS(2, 13);
          }
        }
        if (lane == 0) {
          bulk_wait();
          mbar_arrive_n(sb + B_CS2, 2);
          TS(2, 52);
        }
        mbar_wait(sb + B_KVPART, 0, left);
      }
      if (lane == 0) {
        if (warp == 8) {
#pragma unroll 1
          for (int c = P1WIN - 1; c < 8; c++) {
            const uint32_t bar = sb + B_FULL + 8 * c, live = c >= P1WIN;
            mbar_wait(live ? bar - 8 * P1WIN : sb + B_OUT, !live, left);
            mbar_wait(sb + (c < 4 ? B_OUT : B_EMPTY + 8 * (c & 3)), c < 4, left);
            p1_load_w(live, bar, sb + RING + (c & 3) * QSLOT, &prm.map[6], 64 * j, 64 * c, &prm.map[1], FS * j);
            TS(2, 44 + c);
          }
#pragma unroll 1
          for (int c = 0; c < 8; c++) {
            const uint32_t bar = sb + B_FULL + 8 * c, dst = sb + RING + (c & 3) * QSLOT;
            mbar_wait(sb + B_EMPTY + 8 * ((c + 4) & 7), c >> 2, left);
            mbar_expect_tx(bar, QSLOT);
            tma2d(dst, &prm.map[1], FS * j + 64, 64 * c, bar);
            tma2d(dst + 8192, &prm.map[0], 64 * j, 64 * c, bar);
            tma2d(dst + 16384, &prm.map[1], FS * j + 128, 64 * c, bar);
            TS(2, 20 + c);
          }
        }
#pragma unroll 1
        for (int n = 8 * (warp - 8); n < 8 * (warp - 7); n++) {
          const uint32_t job = prm.jobs[n];
          const uint32_t bar = sb + B_FULL + ((job >> 1) & 56), part = (job >> 16) & 3;
          const int jj = j ^ (job >> 19);
          mbar_wait(sb + B_EMPTY + 8 * (job & 7), (job >> 3) & 1, left);
          mbar_expect_tx(bar, part == 2 ? 12288 : SLOT);
          tma3d(sb + RING + ((job << 7) & 0x1c000), &prm.map[part < 2 ? 2 : part + 1], 0, part == 3 ? 64 * jj : FS * jj + 64 * part,
                4 * (j & 1) + 2 * (((j >> 1) ^ (job >> 18)) & 1), bar);
        }
      }
    } else {
      const uint32_t epoch = ld_rlx32(&g_epoch[blockIdx.x]), odd = epoch & 1;
      float4* const sum = &g_sum[(odd * 8 + j) * NSUM];
      const int row0 = 32 * i + 16 * (warp - 10), f0 = FS * j + 8 * lane + (lane < 8 ? 64 : 0);
      const bool on = lane < 22 && f0 < F_;
      if (CSWAIT >= 0) mbar_wait(sb + B_FULL + 8 * CSWAIT, 0, left);
      if (lane < 18) g_sum[((odd ^ 1) * 8 + j) * NSUM + i * 36 + (warp - 10) * 18 + lane] = make_float4(0.f, 0.f, 0.f, 0.f);
      {
        int ld = lane < 16 ? 3 * D_ : F_;
        const int ld2 = (lane >> 3) == 1 ? 3 * D_ : F_;
        const __nv_bfloat16* src = (lane < 16 ? wqkv + D_ + (lane >> 3) * D_ + 64 * j + 8 * (lane & 7) : w1 + FS * j + 8 * (lane & 7)) + (size_t)row0 * ld;
        const __nv_bfloat16* src2 = ((lane >> 3) == 1 ? wqkv + 64 * j + 8 * (lane & 7) : w1 + (on ? f0 : FS * j)) + (size_t)row0 * ld2;
        float s[8] = {0.f, 0.f, 0.f, 0.f, 0.f, 0.f, 0.f, 0.f};
#pragma unroll 1
        for (int b = 0; b < 4; b++) {
          uint4 v[8];
#pragma unroll
          for (int k = 0; k < 8; k++) v[k] = ldg_nc128(src + k * ld);
#pragma unroll
          for (int k = 0; k < 8; k++) add8(s, v[k]);
          src += 8 * ld;
          if (b & 1) {
            float4* dst = sum + (b == 1 ? SUM_1 : SUM_2) + lane;
            if (b == 1 ? lane < 24 : on) { red128f(dst, s[0], s[1], s[2], 1.f); red128f(dst + 32, s[3], s[4], s[5], 1.f); red128f(dst + 64, s[6], s[7], 0.f, 1.f); }
#pragma unroll
            for (int k = 0; k < 8; k++) s[k] = 0.f;
            TS(2, 9 + (b >> 1));
            if (b == 1) mbar_wait(sb + B_FULL + 8 * QFWAIT, 0, left);
            src = src2;
            ld = ld2;
          }
        }
      }
      if (warp == 11) {
        mbar_wait(sb + B_CS1, 0, left);
        gather(sum + SUM_2 + lane, on, 22, on && (lane >> 3) != 1 ? b1 + f0 : nullptr, sb + EXT2);
        if (lane == 0) mbar_arrive_n(sb + B_CS2, 2);
        TS(2, 15);
      }
      {
        float4* const kvp = sum + (warp - 10) * 192 + lane;
        float4 v[6];
        mbar_wait(sb + B_KVPART, 0, left);
        TS(2, 12);
#pragma unroll
        for (int h = 0; h < 2; h++) {
          const uint32_t kp = sb + kvpart(2 * (warp - 10) + h, lane);
#pragma unroll
          for (int q = 0; q < 3; q++) {
            const float4 a = lds128f(kp + 2048 * q), b = lds128f(kp + 8192 + 2048 * q);
            red128f(kvp + 32 * (3 * h + q), a.x + b.x, a.y + b.y, a.z + b.z, 1.f);
          }
        }
        TS(2, 11);
        int it = 0;
        while (true) {
          bool done = true;
#pragma unroll
          for (int k = 0; k < 6; k++) v[k] = ld_rlx128f(kvp + 32 * k);
#pragma unroll
          for (int k = 0; k < 6; k++) done = done && v[k].w == 16.f;
          if (__all_sync(0xffffffffu, done) || ++it > SPIN_LIMIT) break;
          __nanosleep(64);
        }
#pragma unroll
        for (int h = 0; h < 2; h++) {
          const float4 a = v[3 * h], b = v[3 * h + 1], c = v[3 * h + 2];
          const int zl = 8 * (lane & 3);
          const float z0 = __shfl_sync(0xffffffffu, c.z, zl), z1 = __shfl_sync(0xffffffffu, c.z, zl + 4);
          const float z2 = __shfl_sync(0xffffffffu, c.z, zl + 1), z3 = __shfl_sync(0xffffffffu, c.z, zl + 5);
          const uint32_t d = sb + KVS + (2 * (warp - 10) + h) * 768 + lane * 4;
          sts32(d, pack(a.x, a.y)); sts32(d + 256, pack(a.z, b.x)); sts32(d + 128, pack(b.y, b.z)); sts32(d + 384, pack(c.x, c.y));
          sts32(d + 512, pack(z0, z1)); sts32(d + 640, pack(z2, z3));
        }
        fence_async();
        __syncwarp();
        if (lane == 0) mbar_arrive_n(sb + B_KVRDY, 2);
        TS(2, 14);
      }
      if (warp == 10 && lane == 0) {
        mbar_wait(sb + B_CS2, 0, left);
        fence_async_all();
        asm volatile("red.release.gpu.global.add.u32 [%0], 1;" ::"l"(&g_flag[i * 32]) : "memory");
        TS(2, 55);
        const unsigned target = 8u * (epoch + 1);
        int it = 0;
        while (true) {
          unsigned v;
          asm volatile("ld.acquire.gpu.global.u32 %0, [%1];" : "=r"(v) : "l"(&g_flag[i * 32]) : "memory");
          if ((int)(v - target) >= 0 || ++it > SPIN_LIMIT) break;
          __nanosleep(128);
        }
        fence_async_all();
        mbar_arrive(sb + B_OUT);
        TS(2, 16);
      }
    }
  } else {
    asm volatile("setmaxnreg.inc.sync.aligned.u32 " STR(CREGS) ";");
    const int w = warp >> 2, wq = warp & 3, t = lane & 3;
    const uint32_t epoch = ld_rlx32(&g_epoch[blockIdx.x]);
    uint32_t dB = ((sb & 0x3ffffu) >> 4) + LBO(8192);
    uint32_t dA = dB + (LBO(16) - LBO(8192) + w * 512);
    constexpr uint32_t TO_NS = LBO(128) - LBO(8192), TO_EX = 0u - LBO(8192);
    auto release = [&](uint32_t bar) INL { if (lane == 0) mbar_arrive(sb + bar); };
    auto next = [&]() INL { dA += prm.zero; dB += prm.zero; wg_fence(); };
    auto turn = [&](int n) INL { if (n == LG0 && w == 1) asm volatile("bar.sync 3, 256;" ::: "memory"); };
    auto pass = [&](int n) INL { if (n == LG0 + LGL && w == 0) asm volatile("bar.arrive 3, 256;" ::: "memory"); };

    float acc1[96];
    uint32_t ea[4];
    float rs0, rs1, rl0, rl1;
    const uint32_t sta = sb + (16 * warp + (lane & 15)) * 128 + (((lane >> 4) ^ (lane & 7)) << 4);
    uint4 xr[4];
    const uint32_t tag = (epoch + 1) & 1;
    float4* const stp = &g_st[(i * 8 + warp) * 8];
    float4 sv;
    const uint32_t zr = prm.zero;
    uint32_t klo = 0x10000u, khi = 0xffff0000u;
    bool ok = false;
    auto xload = [&]() INL {
#pragma unroll
      for (int k = 0; k < 4; k++) xr[k] = ldg_nc128(x + (size_t)(128 * i + 16 * warp + 8 * (lane >> 4) + j) * D_ + 8 * (lane & 15) + 128 * k);
    };
    if constexpr (XL < 0) xload();
    sfor<0, 8>(LAM(C) {
      constexpr int c = C.v;
      if (!ok) mbar_wait(sb + full(c), 0, left);
      TS(w, 1 + c);
      turn(c);
      next();
      sfor<0, 4>(LAM(K) { wg192_ss<0, (c | K.v) != 0>(acc1, dA + c * 1024 + K.v * 2, dB + ((RING + (c & 3) * QSLOT) >> 4) + K.v * 128); });
      wg_commit();
      pass(c);
      if constexpr (c > 0) { wg_wait<1>(); release(empty(c - 1)); }
      if constexpr (c == XL) xload();
      if constexpr (c == ST1) ok = mbar_test(sb + full(c + 1), 0, klo, khi, zr);
      else ok = mbar_test(sb + full(c + 1), par(c + 1));
      if constexpr (c == ST1) {
        float xv[32], s[4] = {0.f, 0.f, 0.f, 0.f};
#pragma unroll
        for (int k = 0; k < 4; k++) {
          const uint32_t u[4] = {xr[k].x, xr[k].y, xr[k].z, xr[k].w};
#pragma unroll
          for (int e = 0; e < 4; e++) {
            xv[8 * k + 2 * e] = __uint_as_float(u[e] * klo); xv[8 * k + 2 * e + 1] = __uint_as_float(u[e] & khi);
            s[e] += xv[8 * k + 2 * e] + xv[8 * k + 2 * e + 1];
          }
        }
        float mu = (s[0] + s[1]) + (s[2] + s[3]);
#pragma unroll
        for (int o = 1; o < 16; o *= 2) mu += __shfl_xor_sync(0xffffffffu, mu, o);
        mu *= -1.f / D_;
        s[0] = s[1] = s[2] = s[3] = 0.f;
#pragma unroll
        for (int k = 0; k < 32; k++) { const float d = xv[k] + mu; s[k & 3] = fmaf(d, d, s[k & 3]); }
        float q = (s[0] + s[1]) + (s[2] + s[3]);
#pragma unroll
        for (int o = 1; o < 16; o *= 2) q += __shfl_xor_sync(0xffffffffu, q, o);
        q = sqrt_(fmaf(q, 1.f / D_, 1e-5f));
        if ((lane & 15) == 0) st_rlx64((uint2*)(stp + j) + (lane >> 4), (__float_as_uint(mu) & ~1u) | tag, (__float_as_uint(q) & ~1u) | tag);
      }
      if constexpr (c == 6) sv = ld_rlx128f(stp + (lane >> 2));
      if constexpr (c == 7) {
        int it = 0;
        while (!__all_sync(0xffffffffu, fresh(sv, tag)) && ++it < SPIN_LIMIT) sv = ld_rlx128f(stp + (lane >> 2));
        TS(w, 43);
        rs0 = rcp(sv.y); rs1 = rcp(sv.w);
        rl0 = rs0 * LOG2E; rl1 = rs1 * LOG2E;
#pragma unroll
        for (int r = 0; r < 2; r++) {
          float v = t == 0 ? (r ? sv.z : sv.x) : (r ? sv.w : sv.y);
          const uint32_t h0 = split(v), h1 = split(v), m = t == 0 ? 0x10001u : t == 1;
          ea[r] = h0 * m;
          ea[2 + r] = h1 * m;
        }
      }
    });
    auto phi16 = [&](auto O, auto& acc, uint32_t* r) INL {
      constexpr int o = O.v;
      reg_fence<o, 8>(acc);
#pragma unroll
      for (int k = 0; k < 4; k++) r[k] = pack(phi(acc[o + 2 * k], k & 1 ? rs1 : rs0, k & 1 ? rl1 : rl0), phi(acc[o + 2 * k + 1], k & 1 ? rs1 : rs0, k & 1 ? rl1 : rl0));
    };
    auto mish16 = [&](auto O, auto& acc, uint32_t* r) INL {
      constexpr int o = O.v;
      constexpr bool sc = sizeof(acc) == 96;
      reg_fence<o, 8>(acc);
#pragma unroll
      for (int k = 0; k < 4; k++) r[k] = pack(mish<sc>(acc[o + 2 * k], k & 1 ? rs1 : rs0, k & 1 ? rl1 : rl0), mish<sc>(acc[o + 2 * k + 1], k & 1 ? rs1 : rs0, k & 1 ? rl1 : rl0));
    };
    auto put = [&](int slot, int a0, int a1, const uint32_t* r) INL {
      const uint32_t st = a1 - a0 > 1 ? after(sta, r[4 * a1 - 1], zr) : sta;
#pragma unroll
      for (int a = a0; a < a1; a++) stsm4((st ^ (a << 5)) + slot * SLOT, r[4 * a], r[4 * a + 1], r[4 * a + 2], r[4 * a + 3]);
    };
    const uint32_t peer = __reduce_max_sync(0xffffffffu, mapa(sb, (j & 1) ^ 1));
    auto send = [&](int part, int pf) INL {
      fence_async();
      if (pf >= 0) mbar_wait(sb + B_PF + pf * 16 + w * 8, 0, left);
      bulk_peer_elect(peer + slotA(part, 1) * SLOT + warp * 2048, sb + slotA(part, 0) * SLOT + warp * 2048, 2048, peer + B_AF + part * 16 + w * 8);
    };
    auto peer_free = [&](int pf) INL { if (lane == 0) mbar_arrive_peer(peer + B_PF + pf * 16 + w * 8); };

    float acc2[88], kva[32], za[4];
    uint32_t pk[16], pa[16];
    sfor<0, 8>(LAM(C) {
      constexpr int c = C.v, n = 8 + c;
      if (!ok) mbar_wait(sb + full(n), 1, left);
      TS(w, 9 + c);
      if constexpr (c == 0) { mbar_wait(sb + B_CS1, 0, left); TS(w, 40); }
      if constexpr (c == 7) { mbar_wait(sb + B_CS2, 0, left); TS(w, 39); }
      turn(n);
      next();
      if constexpr (c == 0) {
        wg192_rs<0, 1, HI_EX>(acc1, ea[0], ea[1], ea[2], ea[3], dB + (TO_EX + (EXT1 >> 4)));
        wg_commit();
      }
      if constexpr (c == 3) {
        const uint32_t dk = dB + w * 512;
        sfor<0, 4>(LAM(K) { wg64_ss_tt<0, K.v != 0>(kva, dk + 1024 + K.v * 128, dk + K.v * 128); });
        sfor<0, 4>(LAM(K) { wg8_ss_tn<0, K.v != 0, HI_SW, HI_NS>(za, dk + K.v * 128, dB + (TO_NS + (ONES >> 4))); });
        wg_commit();
      }
      sfor<0, 4>(LAM(K) { wg176_ss<0, (c | K.v) != 0>(acc2, dA + c * 1024 + K.v * 2, dB + ((RING + (c & 3) * QSLOT) >> 4) + K.v * 128); });
      if constexpr (c == 7) wg176_rs<0, 1, HI_EX>(acc2, ea[0], ea[1], ea[2], ea[3], dB + (TO_EX + (EXT2 >> 4)));
      wg_commit();
      pass(n);
      if constexpr (c == 0) TS(w, 33);
      if constexpr (c == 1) TS(w, 45);
      if constexpr (c == 3) TS(w, 52);
      if constexpr (c == 7) TS(w, 56);
      if constexpr (c < EW) { wg_wait<1>(); release(empty(n - 1)); }
      if constexpr (c == 0) TS(w, 34);
      if constexpr (c == 1) TS(w, 46);
      ok = mbar_test(sb + full(n + 1), par(n + 1));
      if constexpr (c == 0) {
        reg_fence<0, 96>(acc1);
        sfor<0, 2>(LAM(U) { phi16(IC<8 * U.v>{}, acc1, pk + 4 * U.v); pin2(zr, pk[4 * U.v], pk[4 * U.v + 1]); pin2(zr, pk[4 * U.v + 2], pk[4 * U.v + 3]); });
        asm volatile("barrier.cluster.wait.aligned;" ::: "memory");
      }
      if constexpr (c == 1) {
        here(rl0, rl1, zr);
        sfor<2, 4>(LAM(U) { phi16(IC<8 * U.v>{}, acc1, pk + 4 * U.v); });
        put(0, 0, 4, pk);
      }
      if constexpr (c == 2) {
        here(rs0, rs1, zr);
        sfor<0, 4>(LAM(U) {
          constexpr int o = 32 + 8 * U.v;
          stsm4((sta ^ (U.v << 5)) + SLOT, pack(acc1[o] * rs0, acc1[o + 1] * rs0), pack(acc1[o + 2] * rs1, acc1[o + 3] * rs1),
                pack(acc1[o + 4] * rs0, acc1[o + 5] * rs0), pack(acc1[o + 6] * rs1, acc1[o + 7] * rs1));
        });
        fence_async();
        bar_wg(1 + w);
      }
      if constexpr (c >= 3 && c < 7) { here(rl0, rl1, zr); mish16(IC<64 + 8 * (c - 3)>{}, acc1, pa + 4 * (c - 3)); }
      if constexpr (c == 3) {
        reg_fence<0, 32>(kva);
        reg_fence<0, 4>(za);
        const uint32_t kp = after(sb + w * 8192 + kvpart(wq, lane), pa[3], zr);
        const float z = t == 0 ? za[0] : (t == 1 ? za[2] : 0.f);
        sfor<0, 4>(LAM(H) {
          constexpr int h = H.v;
          if (wq == h) {
            sts128f(kp, kva[8 * h], kva[8 * h + 1], kva[8 * h + 2], 0.f);
            sts128f(kp + 2048, kva[8 * h + 3], kva[8 * h + 4], kva[8 * h + 5], 0.f);
            sts128f(kp + 4096, kva[8 * h + 6], kva[8 * h + 7], z, 0.f);
          }
        });
        __syncwarp();
        release(B_KVPART);
      }
      if constexpr (c >= 3 && c < 7) put(slotA(0, 0), c - 3, c - 2, pa);
      if constexpr (c == 0) TS(w, 35);
      if constexpr (c == 1) TS(w, 47);
      if constexpr (c == 3) TS(w, 53);
      if constexpr (c == 7) TS(w, 57);
      if constexpr (c == 7) send(0, 0);
      if constexpr (c == 7) TS(w, 58);
      if constexpr (c >= EW) { wg_wait<1>(); release(empty(n - 1)); }
      if constexpr (c == 7) TS(w, 59);
      if constexpr (c == 4) peer_free(0);
    });

    float accX[64], accY[64], acco[2][24], hc[24];
    uint32_t pq[16], pb[16], pc[12], pd[16];
    auto store_half = [&](float (&acc)[64], int tile, int hb, uint32_t src) INL {
      const uint32_t st = src + (lane & 15) * 128 + (((lane >> 4) ^ (lane & 7)) << 4);
#pragma unroll
      for (int a = 0; a < 4; a++) {
        const float* p = acc + 32 * hb + 8 * a;
        stsm4(st ^ (a << 5), pack(p[0], p[1]), pack(p[2], p[3]), pack(p[4], p[5]), pack(p[6], p[7]));
      }
      fence_async();
      tma2d_add_elect(&prm.map[7], 64 * (4 * (j & 1) + 2 * (((j >> 1) ^ tile) & 1) + hb), 128 * i + 16 * warp, src);
    };
    auto phiq = [&](auto U) INL { constexpr int u = U.v; phi16(IC<32 + 8 * u>{}, acc2, pq + 4 * u); pin2(zr, pq[4 * u], pq[4 * u + 1]); pin2(zr, pq[4 * u + 2], pq[4 * u + 3]); };
    auto ostep = [&](auto H0) INL {
      sfor<H0.v, H0.v + 2>(LAM(H) { constexpr int h = H.v; wg24_rs<12 * (h & 1), 0, HI_NS>(acco[h >> 1], pq[4 * h], pq[4 * h + 1], pq[4 * h + 2], pq[4 * h + 3], dB + (TO_NS + ((KVS + h * 768) >> 4))); });
      wg_commit();
    };
    sfor<0, 16>(LAM(S) {
      constexpr int s = S.v, n = 16 + s, part = partS(s);
      if (!ok) mbar_wait(sb + full(n), par(n), left);
      if constexpr (s == 1 || (s >= 9 && s <= 11)) mbar_wait(sb + B_AF + part * 16 + w * 8, 0, left);
      if constexpr (s == 5) { TS(w, 38); mbar_wait(sb + B_KVRDY, 0, left); }
      TS(w, 17 + s);
      turn(n);
      next();
      if constexpr (s == 5) ostep(IC<0>{});
      if constexpr (s == 3) {
#pragma unroll
        for (int k = 0; k < 64; k++) accY[k] = acc2[k];
      }
      const uint32_t da = dA + slotA(part, peerS(s)) * 1024, db = dB + (LBO(part == 2 ? 6144 : 8192) - LBO(8192) + (8 + s % 6) * 1024);
      auto& acc = *(tileS(s) ? &accY : &accX);
      sfor<0, part == 2 ? 3 : 4>(LAM(K) {
        constexpr int k = K.v, sc = (s != 0 && s != 3) || k != 0;
        if constexpr ((RSM >> s) & 1) {
          const uint32_t* p = (part == 0 ? pa : part == 1 ? pb : part == 2 ? pc : pd) + 4 * k;
          wg128_rs<0, sc, HI_SW>(acc, p[0], p[1], p[2], p[3], db + k * 128);
        } else wg128_ss<0, sc>(acc, da + k * 2, db + k * 128);
      });
      wg_commit();
      pass(n);
      if constexpr (s == 0 || s == 5 || s == 6 || s == 12) { wg_wait<1>(); release(empty(n - 1)); }
      if constexpr (s == 0) { peer_free(1); reg_fence<0, 88>(acc2); }
      if constexpr (s == 5) peer_free(2);
      if constexpr (s < 15) ok = mbar_test(sb + full(n + 1), par(n + 1));
      if constexpr (s == 7) send(3, 2);
      if constexpr (s >= 1 && s <= 4) here(rl0, rl1, zr);
      if constexpr (s < 2) { sfor<2 * s, 2 * s + 2>(LAM(U) { mish16(IC<8 * U.v>{}, acc2, pb + 4 * U.v); }); put(slotA(1, 0), 2 * s, 2 * s + 2, pb); }
      if constexpr (s == 2) {
        sfor<0, 4>(phiq);
#pragma unroll
        for (int k = 0; k < 24; k++) hc[k] = acc2[64 + k] * (k & 2 ? rs1 : rs0);
        rl0 = rl1 = -0.5f;
#pragma unroll
        for (int k = 0; k < 24; k += 4) pin4(zr, hc + k);
        send(1, 1);
      }
      if constexpr (s == 3 || s == 4) { sfor<2 * s - 6, s - 1>(LAM(U) { mish16(IC<8 * U.v>{}, hc, pc + 4 * U.v); }); put(slotA(2, 0), 2 * s - 6, s - 1, pc); }
      if constexpr (s == 5 || s == 6) {
        float (&o)[24] = acco[s - 5];
        reg_fence<0, 24>(o);
#pragma unroll
        for (int h = 0; h < 2; h++) {
          const float r0 = rcp(o[12 * h + 8] + 1e-6f), r1 = rcp(o[12 * h + 10] + 1e-6f);
          uint32_t* r = pd + 4 * (2 * s - 10 + h);
#pragma unroll
          for (int k = 0; k < 4; k++) r[k] = pack(o[12 * h + 2 * k] * (k & 1 ? r1 : r0), o[12 * h + 2 * k + 1] * (k & 1 ? r1 : r0));
        }
        put(slotA(3, 0), 2 * s - 10, 2 * s - 8, pd);
        if constexpr (s == 5) { wg_fence(); ostep(IC<2>{}); send(2, -1); }
      }
      if constexpr (s == 11) { if (lane == 0) mbar_arrive_peer(peer + B_DONE); }
      if constexpr (s == 12) {
        reg_fence<0, 64>(accX);
        mbar_wait(sb + empty(21), par(21), left);
        mbar_wait(sb + B_OUT, 0, left);
      }
      if constexpr (s == 12 || s == 13) store_half(accX, 0, s - 12, sb + (s - 12) * 2 * SLOT + warp * 2048);
      if constexpr (s == 12) TS(w, 49);
      if constexpr (s == 13) TS(w, 48);
      if constexpr ((s >= 1 && s <= 4) || (s >= 7 && s <= 10)) { wg_wait<1>(); release(empty(n - 1)); }
    });
    wg_wait<0>();
    reg_fence<0, 64>(accY);
    TS(w, 50);
    mbar_wait(sb + empty(27), par(27), left);
    store_half(accY, 1, 0, sb + 12 * SLOT + warp * 2048);
    store_half(accY, 1, 1, sb + 13 * SLOT + warp * 2048);
    TS(w, 51);
    bulk_wait_read<0>();
    mbar_wait(sb + B_DONE, 0, left);
    if (threadIdx.x == 0) g_epoch[blockIdx.x] = epoch + 1;
    TS(w, 37);
    TSG(w, 63);
  }
}

typedef CUresult (*EncodeFn)(CUtensorMap*, CUtensorMapDataType, cuuint32_t, void*, const cuuint64_t*, const cuuint64_t*, const cuuint32_t*,
                             const cuuint32_t*, CUtensorMapInterleave, CUtensorMapSwizzle, CUtensorMapL2promotion, CUtensorMapFloatOOBfill);

bool encode(EncodeFn enc, CUtensorMap* m, const void* p, int rank, cuuint64_t d0, cuuint64_t d1, cuuint64_t d2, cuuint64_t s1, cuuint64_t s2,
            cuuint32_t b0, cuuint32_t b1, cuuint32_t b2) {
  cuuint64_t dims[3] = {d0, d1, d2}, strides[2] = {s1, s2};
  cuuint32_t box[3] = {b0, b1, b2}, es[3] = {1, 1, 1};
  return enc(m, CU_TENSOR_MAP_DATA_TYPE_BFLOAT16, rank, (void*)p, dims, strides, box, es, CU_TENSOR_MAP_INTERLEAVE_NONE, CU_TENSOR_MAP_SWIZZLE_128B,
             CU_TENSOR_MAP_L2_PROMOTION_L2_128B, CU_TENSOR_MAP_FLOAT_OOB_FILL_NONE) == CUDA_SUCCESS;
}

constexpr uint32_t job(int s) {
  const int after = s < 6 ? 12 + ((0x332110 >> (4 * s)) & 3) : s + 10;
  return (after & 7) | par(after) << 3 | (s & 7) << 4 | (s % 6) << 7 | partS(s) << 16 | tileS(s) << 18 | peerS(s) << 19;
}

}

extern "C" void kernel_launch(void* const* d_in, const int* in_sizes, int n_in, void* d_out, int out_size) {
  const __nv_bfloat16* x = (const __nv_bfloat16*)d_in[0];
  const __nv_bfloat16* wqkv = (const __nv_bfloat16*)d_in[1];
  const __nv_bfloat16* wo = (const __nv_bfloat16*)d_in[2];
  const __nv_bfloat16* w1 = (const __nv_bfloat16*)d_in[4];
  const __nv_bfloat16* b1 = (const __nv_bfloat16*)d_in[5];
  const __nv_bfloat16* w2 = (const __nv_bfloat16*)d_in[6];
  static EncodeFn enc = nullptr;
  if (!enc) {
    void* fn = nullptr;
    cudaDriverEntryPointQueryResult st;
    if (cudaGetDriverEntryPoint("cuTensorMapEncodeTiled", &fn, cudaEnableDefault, &st) != cudaSuccess || !fn) return;
    enc = (EncodeFn)fn;
    cudaFuncSetAttribute(fused_kernel, cudaFuncAttributeMaxDynamicSharedMemorySize, SMEM_BYTES);
  }
  Params prm;
  bool ok = true;
  ok &= encode(enc, &prm.map[0], wqkv, 2, D_, D_, 1, 3 * D_ * 2, 0, 64, 64, 1);
  ok &= encode(enc, &prm.map[1], w1, 2, F_, D_, 1, F_ * 2, 0, 64, 64, 1);
  ok &= encode(enc, &prm.map[2], w2, 3, 64, F_, 8, D_ * 2, 128, 64, 64, 2);
  ok &= encode(enc, &prm.map[3], w2, 3, 64, F_, 8, D_ * 2, 128, 64, 48, 2);
  ok &= encode(enc, &prm.map[4], wo, 3, 64, D_, 8, D_ * 2, 128, 64, 64, 2);
  ok &= encode(enc, &prm.map[5], x, 2, D_, S_, 1, D_ * 2, 0, 64, 128, 1);
  ok &= encode(enc, &prm.map[6], wqkv + D_, 3, D_, D_, 2, 3 * D_ * 2, D_ * 2, 64, 64, 2);
  ok &= encode(enc, &prm.map[7], d_out, 2, D_, S_, 1, D_ * 2, 0, 64, 16, 1);
  if (!ok) return;
  prm.zero = 0;
  for (int n = 0; n < 16; n++) prm.jobs[n] = job(2 * (n & 7) + (n >> 3));
  fused_kernel<<<128, 384, SMEM_BYTES>>>(prm, x, wqkv, wo, w1, b1, w2, (__nv_bfloat16*)d_out);
}
```

```cpp
#include <cuda_runtime.h>
#include <cuda.h>
#include <cuda_bf16.h>
#include <stdint.h>

namespace {

constexpr int S_ = 2048, D_ = 512, F_ = 1376, FS = 176;

constexpr uint32_t SLOT = 16384;
constexpr uint32_t RING = 8 * SLOT;
constexpr uint32_t QSLOT = 24576;
constexpr uint32_t MISC = 14 * SLOT;
constexpr uint32_t B_FULL = MISC;
constexpr uint32_t B_AF = MISC + 64;
constexpr uint32_t B_EMPTY = MISC + 128;
constexpr uint32_t B_PF = MISC + 192;
constexpr uint32_t B_KVRDY = MISC + 240, B_CS2 = MISC + 248;
constexpr uint32_t B_CS1 = MISC + 256, B_OUT = MISC + 264, B_KVPART = MISC + 272, B_DONE = MISC + 280;
constexpr uint32_t EXT2 = MISC + 320, EXT1 = EXT2 + 22 * 48;
constexpr uint32_t ONES = EXT1 + 24 * 48;
constexpr uint32_t B_SND = MISC + 2816;
constexpr uint32_t KVS = 0;
constexpr uint32_t SMEM_BYTES = 232448;

constexpr int SPIN_LIMIT = 1 << 19;

constexpr int NSUM = 576, SUM_1 = 384, SUM_2 = 480;
__device__ float4 g_sum[2 * 8 * NSUM];
__device__ float4 g_st[16 * 8 * 8];
__device__ unsigned g_flag[16 * 32];
__device__ unsigned g_epoch[128];

__device__ __forceinline__ void mbar_init(uint32_t bar, uint32_t cnt) { asm volatile("mbarrier.init.shared::cta.b64 [%0], %1;" ::"r"(bar), "r"(cnt) : "memory"); }
__device__ __forceinline__ void mbar_expect_tx(uint32_t bar, uint32_t bytes) { asm volatile("mbarrier.arrive.expect_tx.shared::cta.b64 _, [%0], %1;" ::"r"(bar), "r"(bytes) : "memory"); }
__device__ __forceinline__ void mbar_arrive(uint32_t bar) { asm volatile("mbarrier.arrive.shared::cta.b64 _, [%0];" ::"r"(bar) : "memory"); }
__device__ __forceinline__ void mbar_arrive_n(uint32_t bar, uint32_t n) { asm volatile("mbarrier.arrive.shared::cta.b64 _, [%0], %1;" ::"r"(bar), "r"(n) : "memory"); }
__device__ __forceinline__ bool mbar_test(uint32_t bar, uint32_t parity) {
  uint32_t ok;
  asm volatile("{ .reg .pred p; mbarrier.test_wait.parity.shared::cta.b64 p, [%1], %2; selp.u32 %0, 1, 0, p; }" : "=r"(ok) : "r"(bar), "r"(parity) : "memory");
  return ok;
}
__device__ __forceinline__ bool mbar_test(uint32_t bar, uint32_t parity, uint32_t& a, uint32_t& b, uint32_t zero) {
  uint32_t ok;
  asm volatile("{ .reg .pred p; mbarrier.test_wait.parity.shared::cta.b64 p, [%3], %4; selp.u32 %0, 1, 0, p; @p add.u32 %1, %1, %5; @p add.u32 %2, %2, %5; }"
               : "=r"(ok), "+r"(a), "+r"(b) : "r"(bar), "r"(parity), "r"(zero) : "memory");
  return ok;
}
__device__ __forceinline__ void here(float& a, float& b, uint32_t zero) {
  asm volatile("{ .reg .b32 t; mov.u32 t, %%clock; and.b32 t, t, %2; add.f32 %0, %0, t; add.f32 %1, %1, t; }" : "+f"(a), "+f"(b) : "r"(zero) : "memory");
}
__device__ __forceinline__ uint32_t after(uint32_t a, uint32_t v, uint32_t zero) {
  uint32_t r;
  asm("lop3.b32 %0, %1, %2, %3, 0xf8;" : "=r"(r) : "r"(a), "r"(v), "r"(zero));
  return r;
}
__device__ __forceinline__ void mbar_wait(uint32_t bar, uint32_t parity, uint32_t& left) {
  asm volatile("{ .reg .pred p;\n"
               "W: mbarrier.try_wait.parity.shared::cta.b64 p, [%1], %2;\n"
               "@!p sub.u32 %0, %0, 1;\n"
               "setp.gt.and.s32 p, %0, 0, !p;\n"
               "@p bra W; }" : "+r"(left) : "r"(bar), "r"(parity) : "memory");
}
__device__ __forceinline__ void tma2d(uint32_t dst, const CUtensorMap* m, int c0, int c1, uint32_t bar) {
  asm volatile("cp.async.bulk.tensor.2d.shared::cluster.global.mbarrier::complete_tx::bytes [%0], [%1, {%3, %4}], [%2];"
               ::"r"(dst), "l"(m), "r"(bar), "r"(c0), "r"(c1) : "memory");
}
__device__ __forceinline__ void tma3d(uint32_t dst, const CUtensorMap* m, int c0, int c1, int c2, uint32_t bar) {
  asm volatile("cp.async.bulk.tensor.3d.shared::cluster.global.mbarrier::complete_tx::bytes [%0], [%1, {%3, %4, %5}], [%2];"
               ::"r"(dst), "l"(m), "r"(bar), "r"(c0), "r"(c1), "r"(c2) : "memory");
}
__device__ __forceinline__ void tma2d_store(const CUtensorMap* m, int c0, int c1, uint32_t src) {
  asm volatile("cp.async.bulk.tensor.2d.global.shared::cta.tile.bulk_group [%0, {%1, %2}], [%3];" ::"l"(m), "r"(c0), "r"(c1), "r"(src) : "memory");
}
__device__ __forceinline__ void p1_load_w(uint32_t live, uint32_t bar, uint32_t dst, const CUtensorMap* m, int c0, int c1, const CUtensorMap* mf, int cf) {
  asm volatile("{ .reg .pred p; .reg .b32 d; setp.ne.u32 p, %0, 0; add.u32 d, %2, 16384;\n"
               "@p mbarrier.arrive.expect_tx.shared::cta.b64 _, [%1], 40960;\n"
               "@p cp.async.bulk.tensor.3d.shared::cluster.global.mbarrier::complete_tx::bytes [%2], [%3, {%4, %5, %6}], [%1];\n"
               "@p cp.async.bulk.tensor.2d.shared::cluster.global.mbarrier::complete_tx::bytes [d], [%7, {%8, %5}], [%1]; }"
               ::"r"(live), "r"(bar), "r"(dst), "l"(m), "r"(c0), "r"(c1), "r"(0), "l"(mf), "r"(cf) : "memory");
}
__device__ __forceinline__ void p1_load_elect(uint32_t bar, uint32_t dx, const CUtensorMap* mx, int cx, int rx, uint32_t dw, const CUtensorMap* mw, int cw,
                                              const CUtensorMap* mf, int cf) {
  asm volatile("{ .reg .pred p; .reg .b32 d; elect.sync _|p, 0xffffffff; add.u32 d, %5, 16384;\n"
               "@p mbarrier.arrive.expect_tx.shared::cta.b64 _, [%0], 40960;\n"
               "@p cp.async.bulk.tensor.2d.shared::cluster.global.mbarrier::complete_tx::bytes [%1], [%2, {%3, %4}], [%0];\n"
               "@p cp.async.bulk.tensor.3d.shared::cluster.global.mbarrier::complete_tx::bytes [%5], [%6, {%7, %3, %8}], [%0];\n"
               "@p cp.async.bulk.tensor.2d.shared::cluster.global.mbarrier::complete_tx::bytes [d], [%9, {%10, %3}], [%0]; }"
               ::"r"(bar), "r"(dx), "l"(mx), "r"(cx), "r"(rx), "r"(dw), "l"(mw), "r"(cw), "r"(0), "l"(mf), "r"(cf) : "memory");
}
__device__ __forceinline__ void tma2d_add_elect(const CUtensorMap* m, int c0, int c1, uint32_t src) {
  asm volatile("{ .reg .pred p; elect.sync _|p, 0xffffffff;\n"
               "@p cp.reduce.async.bulk.tensor.2d.global.shared::cta.add.tile.bulk_group [%0, {%1, %2}], [%3];\n"
               "@p cp.async.bulk.commit_group; }" ::"l"(m), "r"(c0), "r"(c1), "r"(src) : "memory");
}
__device__ __forceinline__ void bulk_peer_elect(uint32_t dst, uint32_t src, uint32_t bytes, uint32_t bar) {
  asm volatile("{ .reg .pred p; elect.sync _|p, 0xffffffff;\n"
               "@p cp.async.bulk.shared::cluster.shared::cta.mbarrier::complete_tx::bytes [%0], [%1], %2, [%3]; }" ::"r"(dst), "r"(src), "r"(bytes), "r"(bar) : "memory");
}
__device__ __forceinline__ void bulk_commit() { asm volatile("cp.async.bulk.commit_group;" ::: "memory"); }
template <int N> __device__ __forceinline__ void bulk_wait_read() { asm volatile("cp.async.bulk.wait_group.read %0;" ::"n"(N) : "memory"); }
__device__ __forceinline__ void bulk_wait() { asm volatile("cp.async.bulk.wait_group 0;" ::: "memory"); }
__device__ __forceinline__ void bulk_peer(uint32_t dst, uint32_t src, uint32_t bytes, uint32_t bar) {
  asm volatile("cp.async.bulk.shared::cluster.shared::cta.mbarrier::complete_tx::bytes [%0], [%1], %2, [%3];" ::"r"(dst), "r"(src), "r"(bytes), "r"(bar) : "memory");
}
__device__ __forceinline__ void mbar_arrive_peer(uint32_t bar) { asm volatile("mbarrier.arrive.shared::cluster.b64 _, [%0];" ::"r"(bar) : "memory"); }
__device__ __forceinline__ uint32_t mapa(uint32_t a, uint32_t cta) { uint32_t r; asm("mapa.shared::cluster.u32 %0, %1, %2;" : "=r"(r) : "r"(a), "r"(cta)); return r; }
__device__ __forceinline__ void prefetch_map(const CUtensorMap* m) { asm volatile("prefetch.tensormap [%0];" ::"l"(m) : "memory"); }
__device__ __forceinline__ void wg_fence() { asm volatile("wgmma.fence.sync.aligned;" ::: "memory"); }
__device__ __forceinline__ void wg_commit() { asm volatile("wgmma.commit_group.sync.aligned;" ::: "memory"); }
template <int N> __device__ __forceinline__ void wg_wait() { asm volatile("wgmma.wait_group.sync.aligned %0;" ::"n"(N) : "memory"); }
template <int O, int N, int SZ> __device__ __forceinline__ void reg_fence(float (&d)[SZ]) {
#pragma unroll
  for (int k = 0; k < N; k++) asm volatile("" : "+f"(d[O + k])::"memory");
}
__device__ __forceinline__ void fence_async() { asm volatile("fence.proxy.async.shared::cta;" ::: "memory"); }
__device__ __forceinline__ void fence_async_all() { asm volatile("fence.proxy.async;" ::: "memory"); }
__device__ __forceinline__ void bar_wg(int id) { asm volatile("bar.sync %0, 128;" ::"r"(id) : "memory"); }
__device__ __forceinline__ uint32_t pack(float lo, float hi) { uint32_t r; asm("cvt.rn.bf16x2.f32 %0, %1, %2;" : "=r"(r) : "f"(hi), "f"(lo)); return r; }
__device__ __forceinline__ float bflo(uint32_t w) { return __uint_as_float(w << 16); }
__device__ __forceinline__ float bfhi(uint32_t w) { return __uint_as_float(w & 0xffff0000u); }
__device__ __forceinline__ float ex2(float x) { float r; asm("ex2.approx.ftz.f32 %0, %1;" : "=f"(r) : "f"(x)); return r; }
__device__ __forceinline__ float sqrt_(float x) { float r; asm("sqrt.approx.ftz.f32 %0, %1;" : "=f"(r) : "f"(x)); return r; }
__device__ __forceinline__ float rcp(float x) { float r; asm("rcp.approx.ftz.f32 %0, %1;" : "=f"(r) : "f"(x)); return r; }
__device__ __forceinline__ float4 lds128f(uint32_t a) { float4 v; asm volatile("ld.shared.v4.f32 {%0,%1,%2,%3}, [%4];" : "=f"(v.x), "=f"(v.y), "=f"(v.z), "=f"(v.w) : "r"(a) : "memory"); return v; }
__device__ __forceinline__ uint32_t lds32(uint32_t a) { uint32_t v; asm volatile("ld.shared.u32 %0, [%1];" : "=r"(v) : "r"(a) : "memory"); return v; }
__device__ __forceinline__ void sts128(uint32_t a, uint32_t x, uint32_t y, uint32_t z, uint32_t w) { asm volatile("st.shared.v4.u32 [%0], {%1,%2,%3,%4};" ::"r"(a), "r"(x), "r"(y), "r"(z), "r"(w) : "memory"); }
__device__ __forceinline__ void sts128f(uint32_t a, float x, float y, float z, float w) { asm volatile("st.shared.v4.f32 [%0], {%1,%2,%3,%4};" ::"r"(a), "f"(x), "f"(y), "f"(z), "f"(w) : "memory"); }
__device__ __forceinline__ void sts32f(uint32_t a, float x) { asm volatile("st.shared.f32 [%0], %1;" ::"r"(a), "f"(x) : "memory"); }
__device__ __forceinline__ void stsm4(uint32_t a, uint32_t r0, uint32_t r1, uint32_t r2, uint32_t r3) {
  asm volatile("stmatrix.sync.aligned.m8n8.x4.shared.b16 [%0], {%1,%2,%3,%4};" ::"r"(a), "r"(r0), "r"(r1), "r"(r2), "r"(r3) : "memory");
}
__device__ __forceinline__ uint4 ldg_nc128(const void* p) { uint4 v; asm volatile("ld.global.nc.L1::no_allocate.v4.u32 {%0,%1,%2,%3}, [%4];" : "=r"(v.x), "=r"(v.y), "=r"(v.z), "=r"(v.w) : "l"(p)); return v; }
__device__ __forceinline__ float4 ld_rlx128f(const void* p) { float4 v; asm volatile("ld.relaxed.gpu.global.v4.f32 {%0,%1,%2,%3}, [%4];" : "=f"(v.x), "=f"(v.y), "=f"(v.z), "=f"(v.w) : "l"(p) : "memory"); return v; }
__device__ __forceinline__ uint4 ld_rlx128(const void* p) { uint4 v; asm volatile("ld.relaxed.gpu.global.v4.u32 {%0,%1,%2,%3}, [%4];" : "=r"(v.x), "=r"(v.y), "=r"(v.z), "=r"(v.w) : "l"(p) : "memory"); return v; }
__device__ __forceinline__ void red128f(float4* p, float x, float y, float z, float w) { asm volatile("red.relaxed.gpu.global.add.v4.f32 [%0], {%1,%2,%3,%4};" ::"l"(p), "f"(x), "f"(y), "f"(z), "f"(w) : "memory"); }
__device__ __forceinline__ void st_rlx64(void* p, uint32_t x, uint32_t y) { asm volatile("st.relaxed.gpu.global.v2.u32 [%0], {%1,%2};" ::"l"(p), "r"(x), "r"(y) : "memory"); }
__device__ __forceinline__ uint32_t ld_rlx32(const unsigned* p) { uint32_t v; asm volatile("ld.relaxed.gpu.global.u32 %0, [%1];" : "=r"(v) : "l"(p) : "memory"); return v; }
__device__ __forceinline__ void sts32(uint32_t a, uint32_t x) { asm volatile("st.shared.u32 [%0], %1;" ::"r"(a), "r"(x) : "memory"); }
__device__ __forceinline__ float add_sat(float a, float b) { float r; asm("add.sat.f32 %0, %1, %2;" : "=f"(r) : "f"(a), "f"(b)); return r; }
__device__ __forceinline__ void pin(uint32_t& a) { asm volatile("" : "+r"(a)::"memory"); }
__device__ __forceinline__ void pin4(uint32_t zero, uint32_t adr, const float* a) {
  asm volatile("{ .reg .pred p; setp.ne.u32 p, %0, 0; @p st.shared.v4.f32 [%1], {%2, %3, %4, %5}; }" ::"r"(zero), "r"(adr), "f"(a[0]), "f"(a[1]), "f"(a[2]), "f"(a[3]) : "memory");
}
__device__ __forceinline__ void pin4(uint32_t zero, uint32_t adr, const uint32_t* a) {
  asm volatile("{ .reg .pred p; setp.ne.u32 p, %0, 0; @p st.shared.v4.u32 [%1], {%2, %3, %4, %5}; }" ::"r"(zero), "r"(adr), "r"(a[0]), "r"(a[1]), "r"(a[2]), "r"(a[3]) : "memory");
}
__device__ __forceinline__ void pin2(uint32_t zero, uint32_t a, uint32_t b) {
  asm volatile("{ .reg .pred p; setp.ne.u32 p, %0, 0; @p st.shared.v2.u32 [%0], {%1, %2}; }" ::"r"(zero), "r"(a), "r"(b) : "memory");
}
constexpr uint32_t HI_SW = (1024 >> 4) | (1u << 30);
constexpr uint32_t HI_32 = (256 >> 4) | (3u << 30);
constexpr uint32_t HI_NS = 256 >> 4;
constexpr uint32_t HI_EX = 48 >> 4;
#define R8(d, o) "+f"(d[(o)]), "+f"(d[(o) + 1]), "+f"(d[(o) + 2]), "+f"(d[(o) + 3]), "+f"(d[(o) + 4]), "+f"(d[(o) + 5]), "+f"(d[(o) + 6]), "+f"(d[(o) + 7])
template <int O, int SC, uint32_t HA = HI_SW, uint32_t HB = HI_SW, int SZ>
__device__ __forceinline__ void wg192_ss(float (&d)[SZ], uint32_t da, uint32_t db) {
  asm volatile("{ .reg .pred p; .reg .b32 h, k; .reg .b64 a, b; setp.ne.b32 p, %98, 0; mov.b32 h, %99; mov.b32 k, %100; mov.b64 a, {%96, h}; mov.b64 b, {%97, k};\n"
    "wgmma.mma_async.sync.aligned.m64n192k16.f32.bf16.bf16 {%0,%1,%2,%3,%4,%5,%6,%7,%8,%9,%10,%11,%12,%13,%14,%15,%16,%17,%18,%19,%20,%21,%22,%23,%24,%25,%26,%27,%28,%29,%30,%31,%32,%33,%34,%35,%36,%37,%38,%39,%40,%41,%42,%43,%44,%45,%46,%47,%48,%49,%50,%51,%52,%53,%54,%55,%56,%57,%58,%59,%60,%61,%62,%63,%64,%65,%66,%67,%68,%69,%70,%71,%72,%73,%74,%75,%76,%77,%78,%79,%80,%81,%82,%83,%84,%85,%86,%87,%88,%89,%90,%91,%92,%93,%94,%95}, a, b, p, 1, 1, 0, 1; }"
    : R8(d, O + 0), R8(d, O + 8), R8(d, O + 16), R8(d, O + 24), R8(d, O + 32), R8(d, O + 40), R8(d, O + 48), R8(d, O + 56), R8(d, O + 64), R8(d, O + 72), R8(d, O + 80), R8(d, O + 88) : "r"(da), "r"(db), "n"(SC), "n"(HA), "n"(HB));
}

template <int O, int SC, uint32_t HA = HI_SW, uint32_t HB = HI_SW, int SZ>
__device__ __forceinline__ void wg176_ss(float (&d)[SZ], uint32_t da, uint32_t db) {
  asm volatile("{ .reg .pred p; .reg .b32 h, k; .reg .b64 a, b; setp.ne.b32 p, %90, 0; mov.b32 h, %91; mov.b32 k, %92; mov.b64 a, {%88, h}; mov.b64 b, {%89, k};\n"
    "wgmma.mma_async.sync.aligned.m64n176k16.f32.bf16.bf16 {%0,%1,%2,%3,%4,%5,%6,%7,%8,%9,%10,%11,%12,%13,%14,%15,%16,%17,%18,%19,%20,%21,%22,%23,%24,%25,%26,%27,%28,%29,%30,%31,%32,%33,%34,%35,%36,%37,%38,%39,%40,%41,%42,%43,%44,%45,%46,%47,%48,%49,%50,%51,%52,%53,%54,%55,%56,%57,%58,%59,%60,%61,%62,%63,%64,%65,%66,%67,%68,%69,%70,%71,%72,%73,%74,%75,%76,%77,%78,%79,%80,%81,%82,%83,%84,%85,%86,%87}, a, b, p, 1, 1, 0, 1; }"
    : R8(d, O + 0), R8(d, O + 8), R8(d, O + 16), R8(d, O + 24), R8(d, O + 32), R8(d, O + 40), R8(d, O + 48), R8(d, O + 56), R8(d, O + 64), R8(d, O + 72), R8(d, O + 80) : "r"(da), "r"(db), "n"(SC), "n"(HA), "n"(HB));
}

template <int O, int SC, uint32_t HA = HI_SW, uint32_t HB = HI_SW, int SZ>
__device__ __forceinline__ void wg128_ss(float (&d)[SZ], uint32_t da, uint32_t db) {
  asm volatile("{ .reg .pred p; .reg .b32 h, k; .reg .b64 a, b; setp.ne.b32 p, %66, 0; mov.b32 h, %67; mov.b32 k, %68; mov.b64 a, {%64, h}; mov.b64 b, {%65, k};\n"
    "wgmma.mma_async.sync.aligned.m64n128k16.f32.bf16.bf16 {%0,%1,%2,%3,%4,%5,%6,%7,%8,%9,%10,%11,%12,%13,%14,%15,%16,%17,%18,%19,%20,%21,%22,%23,%24,%25,%26,%27,%28,%29,%30,%31,%32,%33,%34,%35,%36,%37,%38,%39,%40,%41,%42,%43,%44,%45,%46,%47,%48,%49,%50,%51,%52,%53,%54,%55,%56,%57,%58,%59,%60,%61,%62,%63}, a, b, p, 1, 1, 0, 1; }"
    : R8(d, O + 0), R8(d, O + 8), R8(d, O + 16), R8(d, O + 24), R8(d, O + 32), R8(d, O + 40), R8(d, O + 48), R8(d, O + 56) : "r"(da), "r"(db), "n"(SC), "n"(HA), "n"(HB));
}

template <int O, int SC, uint32_t HA = HI_SW, uint32_t HB = HI_SW, int SZ>
__device__ __forceinline__ void wg64_ss_tt(float (&d)[SZ], uint32_t da, uint32_t db) {
  asm volatile("{ .reg .pred p; .reg .b32 h, k; .reg .b64 a, b; setp.ne.b32 p, %34, 0; mov.b32 h, %35; mov.b32 k, %36; mov.b64 a, {%32, h}; mov.b64 b, {%33, k};\n"
    "wgmma.mma_async.sync.aligned.m64n64k16.f32.bf16.bf16 {%0,%1,%2,%3,%4,%5,%6,%7,%8,%9,%10,%11,%12,%13,%14,%15,%16,%17,%18,%19,%20,%21,%22,%23,%24,%25,%26,%27,%28,%29,%30,%31}, a, b, p, 1, 1, 1, 1; }"
    : R8(d, O + 0), R8(d, O + 8), R8(d, O + 16), R8(d, O + 24) : "r"(da), "r"(db), "n"(SC), "n"(HA), "n"(HB));
}

template <int O, int SC, uint32_t HA = HI_SW, uint32_t HB = HI_SW, int SZ>
__device__ __forceinline__ void wg8_ss_tn(float (&d)[SZ], uint32_t da, uint32_t db) {
  asm volatile("{ .reg .pred p; .reg .b32 h, k; .reg .b64 a, b; setp.ne.b32 p, %6, 0; mov.b32 h, %7; mov.b32 k, %8; mov.b64 a, {%4, h}; mov.b64 b, {%5, k};\n"
    "wgmma.mma_async.sync.aligned.m64n8k16.f32.bf16.bf16 {%0,%1,%2,%3}, a, b, p, 1, 1, 1, 0; }"
    : "+f"(d[O + 0]), "+f"(d[O + 1]), "+f"(d[O + 2]), "+f"(d[O + 3]) : "r"(da), "r"(db), "n"(SC), "n"(HA), "n"(HB));
}

template <int O, int SC, uint32_t HB, int SZ>
__device__ __forceinline__ void wg192_rs(float (&d)[SZ], uint32_t a0, uint32_t a1, uint32_t a2, uint32_t a3, uint32_t db) {
  asm volatile("{ .reg .pred p; .reg .b32 k; .reg .b64 b; setp.ne.b32 p, %101, 0; mov.b32 k, %102; mov.b64 b, {%100, k};\n"
    "wgmma.mma_async.sync.aligned.m64n192k16.f32.bf16.bf16 {%0,%1,%2,%3,%4,%5,%6,%7,%8,%9,%10,%11,%12,%13,%14,%15,%16,%17,%18,%19,%20,%21,%22,%23,%24,%25,%26,%27,%28,%29,%30,%31,%32,%33,%34,%35,%36,%37,%38,%39,%40,%41,%42,%43,%44,%45,%46,%47,%48,%49,%50,%51,%52,%53,%54,%55,%56,%57,%58,%59,%60,%61,%62,%63,%64,%65,%66,%67,%68,%69,%70,%71,%72,%73,%74,%75,%76,%77,%78,%79,%80,%81,%82,%83,%84,%85,%86,%87,%88,%89,%90,%91,%92,%93,%94,%95}, {%96,%97,%98,%99}, b, p, 1, 1, 1; }"
    : R8(d, O + 0), R8(d, O + 8), R8(d, O + 16), R8(d, O + 24), R8(d, O + 32), R8(d, O + 40), R8(d, O + 48), R8(d, O + 56), R8(d, O + 64), R8(d, O + 72), R8(d, O + 80), R8(d, O + 88) : "r"(a0), "r"(a1), "r"(a2), "r"(a3), "r"(db), "n"(SC), "n"(HB));
}

template <int O, int SC, uint32_t HB, int SZ>
__device__ __forceinline__ void wg176_rs(float (&d)[SZ], uint32_t a0, uint32_t a1, uint32_t a2, uint32_t a3, uint32_t db) {
  asm volatile("{ .reg .pred p; .reg .b32 k; .reg .b64 b; setp.ne.b32 p, %93, 0; mov.b32 k, %94; mov.b64 b, {%92, k};\n"
    "wgmma.mma_async.sync.aligned.m64n176k16.f32.bf16.bf16 {%0,%1,%2,%3,%4,%5,%6,%7,%8,%9,%10,%11,%12,%13,%14,%15,%16,%17,%18,%19,%20,%21,%22,%23,%24,%25,%26,%27,%28,%29,%30,%31,%32,%33,%34,%35,%36,%37,%38,%39,%40,%41,%42,%43,%44,%45,%46,%47,%48,%49,%50,%51,%52,%53,%54,%55,%56,%57,%58,%59,%60,%61,%62,%63,%64,%65,%66,%67,%68,%69,%70,%71,%72,%73,%74,%75,%76,%77,%78,%79,%80,%81,%82,%83,%84,%85,%86,%87}, {%88,%89,%90,%91}, b, p, 1, 1, 1; }"
    : R8(d, O + 0), R8(d, O + 8), R8(d, O + 16), R8(d, O + 24), R8(d, O + 32), R8(d, O + 40), R8(d, O + 48), R8(d, O + 56), R8(d, O + 64), R8(d, O + 72), R8(d, O + 80) : "r"(a0), "r"(a1), "r"(a2), "r"(a3), "r"(db), "n"(SC), "n"(HB));
}

template <int O, int SC, uint32_t HB, int SZ>
__device__ __forceinline__ void wg128_rs(float (&d)[SZ], uint32_t a0, uint32_t a1, uint32_t a2, uint32_t a3, uint32_t db) {
  asm volatile("{ .reg .pred p; .reg .b32 k; .reg .b64 b; setp.ne.b32 p, %69, 0; mov.b32 k, %70; mov.b64 b, {%68, k};\n"
    "wgmma.mma_async.sync.aligned.m64n128k16.f32.bf16.bf16 {%0,%1,%2,%3,%4,%5,%6,%7,%8,%9,%10,%11,%12,%13,%14,%15,%16,%17,%18,%19,%20,%21,%22,%23,%24,%25,%26,%27,%28,%29,%30,%31,%32,%33,%34,%35,%36,%37,%38,%39,%40,%41,%42,%43,%44,%45,%46,%47,%48,%49,%50,%51,%52,%53,%54,%55,%56,%57,%58,%59,%60,%61,%62,%63}, {%64,%65,%66,%67}, b, p, 1, 1, 1; }"
    : R8(d, O + 0), R8(d, O + 8), R8(d, O + 16), R8(d, O + 24), R8(d, O + 32), R8(d, O + 40), R8(d, O + 48), R8(d, O + 56) : "r"(a0), "r"(a1), "r"(a2), "r"(a3), "r"(db), "n"(SC), "n"(HB));
}

template <int O, int SC, uint32_t HB, int SZ>
__device__ __forceinline__ void wg24_rs(float (&d)[SZ], uint32_t a0, uint32_t a1, uint32_t a2, uint32_t a3, uint32_t db) {
  asm volatile("{ .reg .pred p; .reg .b32 k; .reg .b64 b; setp.ne.b32 p, %17, 0; mov.b32 k, %18; mov.b64 b, {%16, k};\n"
    "wgmma.mma_async.sync.aligned.m64n24k16.f32.bf16.bf16 {%0,%1,%2,%3,%4,%5,%6,%7,%8,%9,%10,%11}, {%12,%13,%14,%15}, b, p, 1, 1, 0; }"
    : R8(d, O + 0), "+f"(d[O + 8]), "+f"(d[O + 9]), "+f"(d[O + 10]), "+f"(d[O + 11]) : "r"(a0), "r"(a1), "r"(a2), "r"(a3), "r"(db), "n"(SC), "n"(HB));
}

template <int V> struct IC { static constexpr int v = V; };
template <int I, int N, class Fn> __device__ __forceinline__ void sfor(Fn&& f) {
  if constexpr (I < N) { f(IC<I>{}); sfor<I + 1, N>(f); }
}
#define LAM(X) [&](auto X) __attribute__((always_inline))
#define INL __attribute__((always_inline))

__host__ __device__ constexpr uint32_t LBO(uint32_t b) { return (b >> 4) << 16; }
constexpr float LOG2E = 1.4426950408889634f;
constexpr int P1WIN = 2;
constexpr int XL = 1, ST1 = 3, ST2 = 4, SVL = 6;
constexpr int QFWAIT = 7, GC = 5;
constexpr int SH = 2;
constexpr int VS = 2, KP = 3;
constexpr uint32_t PHS = 0x44444442, MSS = 0x44321000;
constexpr int RSM = 0xa4;
constexpr int WE = 2, LAG = 28;
__host__ __device__ constexpr int cum(uint32_t t, int c) { return c < 0 ? 0 : (t >> (4 * c)) & 15; }
__host__ __device__ constexpr uint32_t full(int n) { return B_FULL + 8 * (n & 7); }
__host__ __device__ constexpr uint32_t empty(int n) { return B_EMPTY + 8 * (n & 7); }
__host__ __device__ constexpr int par(int n) { return (n >> 3) & 1; }
__host__ __device__ constexpr int tileS(int s) { return (0xfc18 >> s) & 1; }
__host__ __device__ constexpr int partS(int s) { return (int)((0x3213213231200100ull >> (4 * s)) & 15); }
__host__ __device__ constexpr int peerS(int s) { return (0x1f52 >> s) & 1; }
__host__ __device__ constexpr int slotA(int part, int peer) { return ((peer ? 0x3753 : 0x1642) >> (4 * part)) & 15; }

struct alignas(64) Params {
  CUtensorMap map[8];
  uint32_t zero;
  uint32_t jobs[16];
};


__device__ __forceinline__ float phi(float u, float rs, float rl) {
  return fmaxf(add_sat(ex2(u * rl), 1e-6f), fmaf(u, rs, 1.000001f));
}
template <bool SCALED> __device__ __forceinline__ float mish(float u, float rs, float rl) {
  const float v = ex2(SCALED ? fmaf(u, LOG2E, rl) : fmaf(u, rl, -0.5f)), h = SCALED ? u : u * rs;
  return fmaf(-h, rcp(fmaf(v, v + 1.41421356237f, 1.f)), h);
}
__device__ __forceinline__ uint32_t split(float& v) { const uint32_t h = pack(v, 0.f); v -= bflo(h); return h; }

__device__ __forceinline__ bool fresh(const float4& a, uint32_t tag) {
  return !(((__float_as_uint(a.x) ^ tag) | (__float_as_uint(a.y) ^ tag) | (__float_as_uint(a.z) ^ tag) | (__float_as_uint(a.w) ^ tag)) & 1);
}
__device__ __forceinline__ uint32_t kvpart(int h, int lane) { return SLOT + (lane >> 1) * 128 + (((2 * h + (lane & 1)) ^ ((lane >> 1) & 7)) << 4); }
__device__ __forceinline__ void add8(float (&s)[8], const uint4& v) {
  s[0] += bflo(v.x); s[1] += bfhi(v.x); s[2] += bflo(v.y); s[3] += bfhi(v.y);
  s[4] += bflo(v.z); s[5] += bfhi(v.z); s[6] += bflo(v.w); s[7] += bfhi(v.w);
}

__global__ void __cluster_dims__(2, 1, 1) __launch_bounds__(384, 1)
fused_kernel(const __grid_constant__ Params prm, const __nv_bfloat16* __restrict__ x, const __nv_bfloat16* __restrict__ wqkv,
             const __nv_bfloat16* __restrict__ wo, const __nv_bfloat16* __restrict__ w1, const __nv_bfloat16* __restrict__ b1,
             const __nv_bfloat16* __restrict__ w2, __nv_bfloat16* __restrict__ out) {
  extern __shared__ __align__(1024) uint8_t smem_raw[];
  const uint32_t sb = __reduce_max_sync(0xffffffffu, (uint32_t)__cvta_generic_to_shared(smem_raw));
  const int i = blockIdx.x >> 3, j = blockIdx.x & 7;
  const int warp = __reduce_max_sync(0xffffffffu, threadIdx.x >> 5);
  const int lane = threadIdx.x & 31;
  uint32_t left = 1u << 16;
  if (warp == 8) {
    if (lane == 0) {
#pragma unroll
      for (int c = 0; c < P1WIN; c++) mbar_init(sb + B_FULL + 8 * c, 1);
      asm volatile("fence.mbarrier_init.release.cluster;" ::: "memory");
    }
    __syncwarp();
#pragma unroll
    for (int c = 0; c < P1WIN; c++) p1_load_elect(sb + B_FULL + 8 * c, sb + c * SLOT, &prm.map[5], 64 * c, 128 * i, sb + RING + c * QSLOT, &prm.map[6], 64 * j, &prm.map[1], FS * j);
  } else if (warp < 8) {
    if (lane == 0) {
      if (warp >= P1WIN) mbar_init(sb + MISC + 8 * warp, 1);
#pragma unroll
      for (int k = 1; k < 4; k++) mbar_init(sb + MISC + 64 * k + 8 * warp, k == 1 ? 1 : (k == 2 ? 8 : 4));
      if (warp < 4) mbar_init(sb + MISC + 256 + 8 * warp, warp < 2 ? 1 : 8);
      mbar_init(sb + B_SND + 8 * warp, warp < 2 || warp >= 6 ? 8 : 4);
      if (warp < 2) mbar_init(sb + B_SND + 64 + 8 * warp, 4);
      asm volatile("fence.mbarrier_init.release.cluster;" ::: "memory");
    }
  } else if (warp == 9) {
    if (lane < 16) sts128(sb + ONES + lane * 16, 0x3f803f80u, 0x3f803f80u, 0x3f803f80u, 0x3f803f80u);
  }
  __syncthreads();
  asm volatile("barrier.cluster.arrive.relaxed.aligned;" ::: "memory");

  if (warp >= 8) {
    asm volatile("setmaxnreg.dec.sync.aligned.u32 72;");
    auto gather = [&](const float4* p, bool on, int lanes, const __nv_bfloat16* bias, uint32_t dst) INL {
      const uint4 bv = bias ? ldg_nc128(bias) : make_uint4(0, 0, 0, 0);
      float4 a, b, c;
      int it = 0;
      while (true) {
        a = ld_rlx128f(p); b = ld_rlx128f(p + 32); c = ld_rlx128f(p + 64);
        if (__all_sync(0xffffffffu, !on || (a.w == 32.f && b.w == 32.f && c.w == 32.f)) || ++it > SPIN_LIMIT) break;
        __nanosleep(32);
      }
      const float v[8] = {a.x, a.y, a.z, b.x, b.y, b.z, c.x, c.y};
      uint32_t h[4], r[4];
#pragma unroll
      for (int k = 0; k < 4; k++) { h[k] = pack(v[2 * k], v[2 * k + 1]); r[k] = pack(v[2 * k] - bflo(h[k]), v[2 * k + 1] - bfhi(h[k])); }
      if (lane < lanes) {
        sts128(dst + 48 * lane, h[0], h[1], h[2], h[3]);
        sts128(dst + 48 * lane + 16, r[0], r[1], r[2], r[3]);
        sts128(dst + 48 * lane + 32, bv.x, bv.y, bv.z, bv.w);
      }
      fence_async();
      __syncwarp();
    };
    if (warp <= 9) {
      if (warp == 9) {
        if (lane == 0) {
#pragma unroll
          for (int k = 0; k < 8; k++) mbar_expect_tx(sb + B_AF + 8 * k, (k >> 1) == 2 ? 6144 : 8192);
#pragma unroll
          for (int k = 0; k < 5; k++) if (k != 1) prefetch_map(&prm.map[k]);
        }
        const float4* const sum = &g_sum[((ld_rlx32(&g_epoch[blockIdx.x]) & 1) * 8 + j) * NSUM];
#pragma unroll 1
        for (int c = 0; c < 8; c++) {
          mbar_wait(sb + B_FULL + 8 * c, 0, left);
          if (lane == 0 && c < 8 - P1WIN) tma2d(sb + (c + P1WIN) * SLOT, &prm.map[5], 64 * (c + P1WIN), 128 * i, sb + B_FULL + 8 * (c + P1WIN));
          if (lane == 0) {
#pragma unroll 1
            for (int q = c < SH ? 8 : c - SH; q < (c == 7 ? 8 : c - SH + 1); q++) tma2d_store(&prm.map[7], 64 * q, 128 * i + 16 * j, sb + q * SLOT + 2048 * j);
            bulk_commit();
          }
          if (c == GC) {
            gather(sum + SUM_1 + lane, lane < 24, 24, (lane >> 3) == 2 ? b1 + FS * j + 8 * (lane - 16) : nullptr, sb + EXT1);
            if (lane == 0) { bulk_wait_read<GC - 3 - SH>(); mbar_arrive(sb + B_CS1); }
          }
        }
        if (lane == 0) {
          bulk_wait();
          mbar_arrive_n(sb + B_CS2, 2);
          fence_async_all();
          asm volatile("red.release.gpu.global.add.u32 [%0], 1;" ::"l"(&g_flag[i * 32]) : "memory");
        }
        mbar_wait(sb + B_KVPART, 0, left);
      }
      if (lane == 0) {
        if (warp == 8) {
#pragma unroll 1
          for (int c = P1WIN - 1; c < 8; c++) {
            const uint32_t bar = sb + B_FULL + 8 * c, live = c >= P1WIN;
            mbar_wait(live ? bar - 8 * P1WIN : sb + B_OUT, !live, left);
            mbar_wait(sb + (c < 4 ? B_OUT : B_EMPTY + 8 * (c & 3)), c < 4, left);
            p1_load_w(live, bar, sb + RING + (c & 3) * QSLOT, &prm.map[6], 64 * j, 64 * c, &prm.map[1], FS * j);
          }
#pragma unroll 1
          for (int c = 0; c < 8; c++) {
            const uint32_t bar = sb + B_FULL + 8 * c, dst = sb + RING + (c & 3) * QSLOT;
            mbar_wait(sb + B_EMPTY + 8 * ((c + 4) & 7), c >> 2, left);
            mbar_expect_tx(bar, QSLOT);
            tma2d(dst, &prm.map[1], FS * j + 64, 64 * c, bar);
            tma2d(dst + 8192, &prm.map[0], 64 * j, 64 * c, bar);
            tma2d(dst + 16384, &prm.map[1], FS * j + 128, 64 * c, bar);
          }
        }
#pragma unroll 1
        for (int n = 8 * (warp - 8); n < 8 * (warp - 7); n++) {
          const uint32_t job = prm.jobs[n];
          const uint32_t bar = sb + B_FULL + ((job >> 1) & 56), part = (job >> 16) & 3;
          const int jj = j ^ (job >> 19);
          mbar_wait(sb + B_EMPTY + 8 * (job & 7), (job >> 3) & 1, left);
          mbar_expect_tx(bar, part == 2 ? 12288 : SLOT);
          tma3d(sb + RING + ((job << 7) & 0x1c000), &prm.map[part < 2 ? 2 : part + 1], 0, part == 3 ? 64 * jj : FS * jj + 64 * part,
                4 * (j & 1) + 2 * (((j >> 1) ^ (job >> 18)) & 1), bar);
        }
      }
    } else {
      const uint32_t epoch = ld_rlx32(&g_epoch[blockIdx.x]), odd = epoch & 1;
      float4* const sum = &g_sum[(odd * 8 + j) * NSUM];
      const int row0 = 32 * i + 16 * (warp - 10), f0 = FS * j + 8 * lane + (lane < 8 ? 64 : 0);
      const bool on = lane < 22 && f0 < F_;
      mbar_wait(sb + B_FULL, 0, left);
      if (lane < 18) g_sum[((odd ^ 1) * 8 + j) * NSUM + i * 36 + (warp - 10) * 18 + lane] = make_float4(0.f, 0.f, 0.f, 0.f);
      {
        const int r = row0 + (lane >> 3), fc = FS * j + 128 + 8 * (lane & 7);
        const __nv_bfloat16* pa = wqkv + (size_t)r * (3 * D_) + D_ + 64 * j + 8 * (lane & 7);
        const __nv_bfloat16* pb = w1 + (size_t)r * F_ + FS * j + 8 * (lane & 7);
        const __nv_bfloat16* pc = pa + D_;
        int lc = 4 * 3 * D_;
#pragma unroll 1
        for (int h = 0; h < 2; h++) {
          uint4 v[12];
#pragma unroll
          for (int k = 0; k < 4; k++) { v[k] = ldg_nc128(pa + 4 * k * 3 * D_); v[4 + k] = ldg_nc128(pb + 4 * k * F_); v[8 + k] = ldg_nc128(pc + k * lc); }
          float s[8];
#pragma unroll
          for (int b = 0; b < 3; b++) {
            float u[8] = {0.f, 0.f, 0.f, 0.f, 0.f, 0.f, 0.f, 0.f};
#pragma unroll
            for (int k = 0; k < 4; k++) add8(u, v[4 * b + k]);
            const bool mine = b == 0 || (lane >> 3) == (b == 1 ? 2 - 2 * h : 1 + h);
#pragma unroll
            for (int k = 0; k < 8; k++) {
              u[k] += __shfl_xor_sync(0xffffffffu, u[k], 8);
              u[k] += __shfl_xor_sync(0xffffffffu, u[k], 16);
              if (mine) s[k] = u[k];
            }
          }
          float4* dst = sum + (h ? SUM_2 : SUM_1) + lane;
          if (h ? on : lane < 24) { red128f(dst, s[0], s[1], s[2], 1.f); red128f(dst + 32, s[3], s[4], s[5], 1.f); red128f(dst + 64, s[6], s[7], 0.f, 1.f); }
          if (h == 0) mbar_wait(sb + B_FULL + 8 * QFWAIT, 0, left);
          pa -= D_;
          pc = pb + (fc < F_ ? 128 : 0);
          pb += 64;
          lc = 4 * F_;
        }
      }
      if (warp == 11) {
        mbar_wait(sb + B_CS1, 0, left);
        gather(sum + SUM_2 + lane, on, 22, on && (lane >> 3) != 1 ? b1 + f0 : nullptr, sb + EXT2);
        if (lane == 0) mbar_arrive_n(sb + B_CS2, 2);
      }
      {
        float4* const kvp = sum + (warp - 10) * 192 + lane;
        float4 v[6];
        mbar_wait(sb + B_KVPART, 0, left);
#pragma unroll
        for (int h = 0; h < 2; h++) {
          const uint32_t kp = sb + kvpart(2 * (warp - 10) + h, lane);
          const float4 a = lds128f(kp), b = lds128f(kp + 8192), c = lds128f(kp + 2048), d = lds128f(kp + 8192 + 2048);
          const float z = __uint_as_float(lds32(kp + 4096)) + __uint_as_float(lds32(kp + 8192 + 4096));
          red128f(kvp + 96 * h, a.x + b.x, a.y + b.y, a.z + b.z, 1.f);
          red128f(kvp + 96 * h + 32, a.w + b.w, c.x + d.x, c.y + d.y, 1.f);
          red128f(kvp + 96 * h + 64, c.z + d.z, c.w + d.w, z, 1.f);
        }
        int it = 0;
        while (true) {
          bool done = true;
#pragma unroll
          for (int k = 0; k < 6; k++) v[k] = ld_rlx128f(kvp + 32 * k);
#pragma unroll
          for (int k = 0; k < 6; k++) done = done && v[k].w == 16.f;
          if (__all_sync(0xffffffffu, done) || ++it > SPIN_LIMIT) break;
          __nanosleep(64);
        }
#pragma unroll
        for (int h = 0; h < 2; h++) {
          const float4 a = v[3 * h], b = v[3 * h + 1], c = v[3 * h + 2];
          const int zl = 8 * (lane & 3);
          const float z0 = __shfl_sync(0xffffffffu, c.z, zl), z1 = __shfl_sync(0xffffffffu, c.z, zl + 4);
          const float z2 = __shfl_sync(0xffffffffu, c.z, zl + 1), z3 = __shfl_sync(0xffffffffu, c.z, zl + 5);
          const uint32_t d = sb + KVS + (2 * (warp - 10) + h) * 768 + lane * 4;
          sts32(d, pack(a.x, a.y)); sts32(d + 256, pack(a.z, b.x)); sts32(d + 128, pack(b.y, b.z)); sts32(d + 384, pack(c.x, c.y));
          sts32(d + 512, pack(z0, z1)); sts32(d + 640, pack(z2, z3));
        }
        fence_async();
        __syncwarp();
        if (lane == 0) mbar_arrive_n(sb + B_KVRDY, 2);
      }
      if (warp == 10 && lane == 0) {
        const unsigned target = 8u * (epoch + 1);
        int it = 0;
        while (true) {
          unsigned v;
          asm volatile("ld.acquire.gpu.global.u32 %0, [%1];" : "=r"(v) : "l"(&g_flag[i * 32]) : "memory");
          if ((int)(v - target) >= 0 || ++it > SPIN_LIMIT) break;
          __nanosleep(128);
        }
        fence_async_all();
        mbar_arrive(sb + B_OUT);
      }
      if (lane == 0) {
        const uint32_t w = warp - 10, peer = mapa(sb, (j & 1) ^ 1);
#pragma unroll 1
        for (int k = 0; k < 4; k++) {
          const uint32_t part = (k + 3) >> 1, o = (~k & 1) * (k ? 4096 : 0) + w * 8192;
          uint32_t dst = peer + slotA(part, 1) * SLOT + o, src = sb + slotA(part, 0) * SLOT + o, len = k == 0 ? 8192 : k == 2 ? 2048 : 4096, bar = peer + B_AF + 16 * part + 8 * w;
          pin(dst); pin(src); pin(len); pin(bar);
          mbar_wait(sb + B_SND + 16 * k + 8 * w, 0, left);
          fence_async();
          bulk_peer(dst, src, len, bar);
        }
        if (w == 0) g_epoch[blockIdx.x] = epoch + 1;
      }
    }
  } else {
    asm volatile("setmaxnreg.inc.sync.aligned.u32 216;");
    const int w = warp >> 2, wq = warp & 3, t = lane & 3;
    const uint32_t epoch = ld_rlx32(&g_epoch[blockIdx.x]);
    uint32_t dB = ((sb & 0x3ffffu) >> 4) + LBO(8192);
    uint32_t dA = dB + (LBO(16) - LBO(8192) + w * 512);
    constexpr uint32_t TO_NS = LBO(128) - LBO(8192), TO_EX = 0u - LBO(8192);
    auto release = [&](uint32_t bar) INL { if (lane == 0) mbar_arrive(sb + bar); };
    auto next = [&]() INL { dA += prm.zero; dB += prm.zero; wg_fence(); };
    auto turn = [&](int n) INL { if (n == LAG && w == 0) asm volatile("bar.sync 3, 256;" ::: "memory"); };
    auto pass = [&](int n) INL { if (n == LAG + 3 && w != 0) asm volatile("bar.arrive 3, 256;" ::: "memory"); };

    float acc1[96];
    uint32_t ea[4];
    float rs0, rs1, rl0, rl1;
    const uint32_t sta = sb + (16 * warp + (lane & 15)) * 128 + (((lane >> 4) ^ (lane & 7)) << 4);
    uint4 xr[4];
    float x0, s1, s2;
    const uint32_t tag = (epoch + 1) & 1;
    float4* const stp = &g_st[(i * 8 + warp) * 8];
    float4 sv;
    const uint32_t zr = prm.zero;
    uint32_t klo = 0x10000u, khi = 0xffff0000u;
    bool ok = false;
    auto xload = [&]() INL {
      const __nv_bfloat16* p = x + (size_t)(128 * i + 16 * warp + 8 * (lane >> 4) + j) * D_;
#pragma unroll
      for (int k = 0; k < 4; k++) xr[k] = ld_rlx128(p + 8 * (lane & 15) + 128 * k);
      x0 = bflo(ld_rlx32((const unsigned*)p));
    };
    sfor<0, 8>(LAM(C) {
      constexpr int c = C.v;
      if (!ok) mbar_wait(sb + full(c), 0, left);
      next();
      sfor<0, 4>(LAM(K) { wg192_ss<0, (c | K.v) != 0>(acc1, dA + c * 1024 + K.v * 2, dB + ((RING + (c & 3) * QSLOT) >> 4) + K.v * 128); });
      wg_commit();
      if constexpr (c > 0) { wg_wait<1>(); release(empty(c - 1)); }
      if constexpr (c == XL) xload();
      if constexpr (c == ST1) ok = mbar_test(sb + full(c + 1), 0, klo, khi, zr);
      else ok = mbar_test(sb + full(c + 1), par(c + 1));
      if constexpr (c == ST1) {
        float s[4] = {0.f, 0.f, 0.f, 0.f}, q[4] = {0.f, 0.f, 0.f, 0.f};
#pragma unroll
        for (int k = 0; k < 4; k++) {
          const uint32_t u[4] = {xr[k].x, xr[k].y, xr[k].z, xr[k].w};
#pragma unroll
          for (int e = 0; e < 4; e++) {
            const float d0 = __uint_as_float(u[e] * klo) - x0, d1 = __uint_as_float(u[e] & khi) - x0;
            s[e] += d0 + d1;
            q[e] = fmaf(d0, d0, fmaf(d1, d1, q[e]));
          }
        }
        s1 = (s[0] + s[1]) + (s[2] + s[3]);
        s2 = (q[0] + q[1]) + (q[2] + q[3]);
        pin2(zr, __float_as_uint(s1), __float_as_uint(s2));
      }
      if constexpr (c == ST2) {
        here(s1, s2, zr);
#pragma unroll
        for (int o = 1; o < 16; o *= 2) { s1 += __shfl_xor_sync(0xffffffffu, s1, o); s2 += __shfl_xor_sync(0xffffffffu, s2, o); }
        s1 *= 1.f / D_;
        const float mu = -(x0 + s1), q = sqrt_(fmaxf(fmaf(s2, 1.f / D_, -s1 * s1), 0.f) + 1e-5f);
        if ((lane & 15) == 0) st_rlx64((uint2*)(stp + j) + (lane >> 4), (__float_as_uint(mu) & ~1u) | tag, (__float_as_uint(q) & ~1u) | tag);
      }
      if constexpr (c == SVL) sv = ld_rlx128f(stp + (lane >> 2));
      if constexpr (c == 7) {
        int it = 0;
        while (!__all_sync(0xffffffffu, fresh(sv, tag)) && ++it < SPIN_LIMIT) sv = ld_rlx128f(stp + (lane >> 2));
        rs0 = rcp(sv.y); rs1 = rcp(sv.w);
        rl0 = rs0 * LOG2E; rl1 = rs1 * LOG2E;
#pragma unroll
        for (int r = 0; r < 2; r++) {
          float v = t == 0 ? (r ? sv.z : sv.x) : (r ? sv.w : sv.y);
          const uint32_t h0 = split(v), h1 = split(v), m = t == 0 ? 0x10001u : t == 1;
          ea[r] = h0 * m;
          ea[2 + r] = h1 * m;
        }
      }
    });
    auto phi16 = [&](auto O, auto& acc, uint32_t* r) INL {
      constexpr int o = O.v;
      reg_fence<o, 8>(acc);
#pragma unroll
      for (int k = 0; k < 4; k++) r[k] = pack(phi(acc[o + 2 * k], k & 1 ? rs1 : rs0, k & 1 ? rl1 : rl0), phi(acc[o + 2 * k + 1], k & 1 ? rs1 : rs0, k & 1 ? rl1 : rl0));
    };
    auto mish16 = [&](auto O, auto& acc, uint32_t* r) INL {
      constexpr int o = O.v;
      constexpr bool sc = sizeof(acc) == 96;
      reg_fence<o, 8>(acc);
#pragma unroll
      for (int k = 0; k < 4; k++) r[k] = pack(mish<sc>(acc[o + 2 * k], k & 1 ? rs1 : rs0, k & 1 ? rl1 : rl0), mish<sc>(acc[o + 2 * k + 1], k & 1 ? rs1 : rs0, k & 1 ? rl1 : rl0));
    };
    auto put = [&](int slot, int a0, int a1, const uint32_t* r) INL {
      const uint32_t st = a1 - a0 > 1 ? after(sta, r[4 * a1 - 1], zr) : sta;
#pragma unroll
      for (int a = a0; a < a1; a++) stsm4((st ^ (a << 5)) + slot * SLOT, r[4 * a], r[4 * a + 1], r[4 * a + 2], r[4 * a + 3]);
    };
    auto put32 = [&](int slot, int a0, int a1, const uint32_t* r, int piece) INL {
      const uint32_t s32 = sb + w * 8192 + (16 * wq + (lane & 15)) * 32 + (((lane >> 4) ^ ((lane >> 2) & 1)) << 4);
      const uint32_t st = a1 - a0 > 1 ? after(s32, r[4 * a1 - 1], zr) : s32;
#pragma unroll
      for (int a = a0; a < a1; a++) stsm4(st + a * 2048 + slot * SLOT, r[4 * a], r[4 * a + 1], r[4 * a + 2], r[4 * a + 3]);
      __syncwarp();
      if (piece < 4) release(B_SND + 16 * piece + 8 * w);
    };
    const uint32_t peer = __reduce_max_sync(0xffffffffu, mapa(sb, (j & 1) ^ 1));
    auto send = [&](int part, int pf) INL {
      fence_async();
      mbar_wait(sb + B_PF + pf * 16 + w * 8, 0, left);
      bulk_peer_elect(peer + slotA(part, 1) * SLOT + warp * 2048, sb + slotA(part, 0) * SLOT + warp * 2048, 2048, peer + B_AF + part * 16 + w * 8);
    };
    auto peer_free = [&](uint32_t bar) INL { if (lane == 0) mbar_arrive_peer(peer + bar + w * 8); };

    float acc2[88], kva[32], za[4];
    uint32_t pk[16], pa[16];
    sfor<0, 8>(LAM(C) {
      constexpr int c = C.v, n = 8 + c;
      if (!ok) mbar_wait(sb + full(n), 1, left);
      if constexpr (c == 0) mbar_wait(sb + B_CS1, 0, left);
      if constexpr (c == 7) mbar_wait(sb + B_CS2, 0, left);
      next();
      if constexpr (c == 0) {
        wg192_rs<0, 1, HI_EX>(acc1, ea[0], ea[1], ea[2], ea[3], dB + (TO_EX + (EXT1 >> 4)));
        wg_commit();
      }
      if constexpr (c == VS + 1) {
        const uint32_t dk = dB + w * 512;
        sfor<0, 4>(LAM(K) { wg64_ss_tt<0, K.v != 0>(kva, dk + 1024 + K.v * 128, dk + K.v * 128); });
        sfor<0, 4>(LAM(K) { wg8_ss_tn<0, K.v != 0, HI_SW, HI_NS>(za, dk + K.v * 128, dB + (TO_NS + (ONES >> 4))); });
        wg_commit();
      }
      sfor<0, 4>(LAM(K) { wg176_ss<0, (c | K.v) != 0>(acc2, dA + c * 1024 + K.v * 2, dB + ((RING + (c & 3) * QSLOT) >> 4) + K.v * 128); });
      if constexpr (c == 7) wg176_rs<0, 1, HI_EX>(acc2, ea[0], ea[1], ea[2], ea[3], dB + (TO_EX + (EXT2 >> 4)));
      wg_commit();
      wg_wait<1>();
      release(empty(n - 1));
      ok = mbar_test(sb + full(n + 1), par(n + 1));
      constexpr int p0 = cum(PHS, c - 1), p1 = cum(PHS, c), m0 = cum(MSS, c - 1), m1 = cum(MSS, c);
      if constexpr (c == 0) reg_fence<0, 96>(acc1);
      else if constexpr (p1 > p0 || m1 > m0) here(rl0, rl1, zr);
      sfor<p0, p1>(LAM(U) {
        phi16(IC<8 * U.v>{}, acc1, pk + 4 * U.v);
        if constexpr (p1 < 4) pin4(zr, sta, pk + 4 * U.v);
      });
      sfor<m0, m1>(LAM(U) {
        mish16(IC<64 + 8 * U.v>{}, acc1, pa + 4 * U.v);
        if constexpr (c < 3) pin4(zr, sta, pa + 4 * U.v);
      });
      if constexpr (c == 0) asm volatile("barrier.cluster.wait.aligned;" ::: "memory");
      if constexpr (p1 == 4 && p0 < 4) put(0, 0, 4, pk);
      if constexpr (c == VS) {
        here(rs0, rs1, zr);
        sfor<0, 4>(LAM(U) {
          constexpr int o = 32 + 8 * U.v;
          stsm4((sta ^ (U.v << 5)) + SLOT, pack(acc1[o] * rs0, acc1[o + 1] * rs0), pack(acc1[o + 2] * rs1, acc1[o + 3] * rs1),
                pack(acc1[o + 4] * rs0, acc1[o + 5] * rs0), pack(acc1[o + 6] * rs1, acc1[o + 7] * rs1));
        });
        fence_async();
        bar_wg(1 + w);
      }
      if constexpr (c == KP) {
        reg_fence<0, 32>(kva);
        reg_fence<0, 4>(za);
        const uint32_t kp = m1 > m0 ? after(sb + w * 8192 + kvpart(wq, lane), pa[4 * m1 - 1], zr) : sb + w * 8192 + kvpart(wq, lane);
        const float z = t == 0 ? za[0] : (t == 1 ? za[2] : 0.f);
        sfor<0, 4>(LAM(H) {
          constexpr int h = H.v;
          if (wq == h) {
            sts128f(kp, kva[8 * h], kva[8 * h + 1], kva[8 * h + 2], kva[8 * h + 3]);
            sts128f(kp + 2048, kva[8 * h + 4], kva[8 * h + 5], kva[8 * h + 6], kva[8 * h + 7]);
          }
        });
        sts32f(kp + 4096, z);
        __syncwarp();
        release(B_KVPART);
      }
      if constexpr (c >= 3 && m1 > (c == 3 ? 0 : m0)) put(slotA(0, 0), c == 3 ? 0 : m0, m1, pa);
      if constexpr (c == 7) send(0, 0);
      if constexpr (c == 4) peer_free(B_PF);
    });

    float accX[64], accY[64], acco[2][24], hc[24];
    uint32_t pq[16], pb[16], pc[12], pd[16];
    auto store_half = [&](float (&acc)[64], int tile, int hb, uint32_t src) INL {
      const uint32_t st = src + (lane & 15) * 128 + (((lane >> 4) ^ (lane & 7)) << 4);
#pragma unroll
      for (int a = 0; a < 4; a++) {
        const float* p = acc + 32 * hb + 8 * a;
        stsm4(st ^ (a << 5), pack(p[0], p[1]), pack(p[2], p[3]), pack(p[4], p[5]), pack(p[6], p[7]));
      }
      fence_async();
      tma2d_add_elect(&prm.map[7], 64 * (4 * (j & 1) + 2 * (((j >> 1) ^ tile) & 1) + hb), 128 * i + 16 * warp, src);
    };
    auto phiq = [&](auto U) INL { constexpr int u = U.v; phi16(IC<32 + 8 * u>{}, acc2, pq + 4 * u); pin4(zr, sta, pq + 4 * u); };
    auto ostep = [&](auto H0) INL {
      sfor<H0.v, H0.v + 2>(LAM(H) { constexpr int h = H.v; wg24_rs<12 * (h & 1), 0, HI_NS>(acco[h >> 1], pq[4 * h], pq[4 * h + 1], pq[4 * h + 2], pq[4 * h + 3], dB + (TO_NS + ((KVS + h * 768) >> 4))); });
      wg_commit();
    };
    sfor<0, 16>(LAM(S) {
      constexpr int s = S.v, n = 16 + s, part = partS(s), XE = 10;
      if (!ok) mbar_wait(sb + full(n), par(n), left);
      if constexpr (s == 1 || s == 6 || s == 8 || s == 9) mbar_wait(sb + B_AF + part * 16 + w * 8, 0, left);
      if constexpr (s == 5) mbar_wait(sb + B_KVRDY, 0, left);
      turn(n);
      next();
      if constexpr (s == 5) ostep(IC<0>{});
      if constexpr (s == 3) {
#pragma unroll
        for (int k = 0; k < 64; k++) accY[k] = acc2[k];
      }
      const uint32_t da = dA + slotA(part, peerS(s)) * 1024, db = dB + (LBO(part == 2 ? 6144 : 8192) - LBO(8192) + (8 + s % 6) * 1024);
      auto& acc = *(tileS(s) ? &accY : &accX);
      sfor<0, part == 2 ? 3 : 4>(LAM(K) {
        constexpr int k = K.v, sc = (s != 0 && s != 3) || k != 0;
        if constexpr ((RSM >> s) & 1) {
          const uint32_t* p = (part == 0 ? pa : part == 1 ? pb : part == 2 ? pc : pd) + 4 * k;
          wg128_rs<0, sc, HI_SW>(acc, p[0], p[1], p[2], p[3], db + k * 128);
        } else if constexpr (part >= 2) wg128_ss<0, sc, HI_32>(acc, da + k * 128, db + k * 128);
        else wg128_ss<0, sc>(acc, da + k * 2, db + k * 128);
      });
      wg_commit();
      pass(n);
      if constexpr (s == 0 || s == 5 || s == 6) { wg_wait<1>(); release(empty(n - 1)); }
      if constexpr (s == XE) { wg_wait<1>(); release(empty(n - 1)); }
      if constexpr (s == 0) { peer_free(B_SND); reg_fence<0, 88>(acc2); }
      if constexpr (s == 5) peer_free(B_SND + 48);
      if constexpr (s < 15) ok = mbar_test(sb + full(n + 1), par(n + 1));
      if constexpr (s == 7) {
        fence_async();
        mbar_wait(sb + B_SND + 48 + w * 8, 0, left);
#pragma unroll
        for (int q = 2; q < 4; q++) bulk_peer_elect(peer + slotA(3, 1) * SLOT + w * 8192 + q * 2048 + wq * 512, sb + slotA(3, 0) * SLOT + w * 8192 + q * 2048 + wq * 512, 512, peer + B_AF + 48 + w * 8);
      }
      if constexpr (s >= 1 && s <= 4) here(rl0, rl1, zr);
      if constexpr (s < 2) { sfor<2 * s, 2 * s + 2>(LAM(U) { mish16(IC<8 * U.v>{}, acc2, pb + 4 * U.v); }); put(slotA(1, 0), 2 * s, 2 * s + 2, pb); }
      if constexpr (s == 1) { __syncwarp(); release(B_SND + 8 * w); }
      if constexpr (s == 2) {
        sfor<0, 4>(phiq);
#pragma unroll
        for (int k = 0; k < 24; k++) hc[k] = acc2[64 + k] * (k & 2 ? rs1 : rs0);
        rl0 = rl1 = -0.5f;
#pragma unroll
        for (int k = 0; k < 24; k += 4) pin4(zr, sta, hc + k);
      }
      if constexpr (s == 3 || s == 4) { sfor<2 * s - 6, s - 1>(LAM(U) { mish16(IC<8 * U.v>{}, hc, pc + 4 * U.v); }); put32(slotA(2, 0), 2 * s - 6, s - 1, pc, s - 2); }
      if constexpr (s == 5 || s == 6) {
        float (&o)[24] = acco[s - 5];
        reg_fence<0, 24>(o);
#pragma unroll
        for (int h = 0; h < 2; h++) {
          const float r0 = rcp(o[12 * h + 8] + 1e-6f), r1 = rcp(o[12 * h + 10] + 1e-6f);
          uint32_t* r = pd + 4 * (2 * s - 10 + h);
#pragma unroll
          for (int k = 0; k < 4; k++) r[k] = pack(o[12 * h + 2 * k] * (k & 1 ? r1 : r0), o[12 * h + 2 * k + 1] * (k & 1 ? r1 : r0));
        }
        put32(slotA(3, 0), 2 * s - 10, 2 * s - 8, pd, s - 2);
        if constexpr (s == 5) { wg_fence(); ostep(IC<2>{}); }
      }
      if constexpr (s == XE - 1) { if (lane == 0) mbar_arrive_peer(peer + B_DONE); }
      if constexpr (s == XE - WE) {
        mbar_wait(sb + empty(21), par(21), left);
        mbar_wait(sb + B_OUT, 0, left);
      }
      if constexpr (s == XE) reg_fence<0, 64>(accX);
      if constexpr (s == XE || s == XE + 1) store_half(accX, 0, s - XE, sb + (s - XE) * 2 * SLOT + warp * 2048);
      if constexpr ((s >= 1 && s <= 4) || (s >= 7 && s < XE) || s == 12) { wg_wait<1>(); release(empty(n - 1)); }
    });
    mbar_wait(sb + empty(27), par(27), left);
    wg_wait<0>();
    reg_fence<0, 64>(accY);
    store_half(accY, 1, 0, sb + 12 * SLOT + warp * 2048);
    store_half(accY, 1, 1, sb + 13 * SLOT + warp * 2048);
    mbar_wait(sb + B_DONE, 0, left);
    bulk_wait_read<0>();
  }
}

typedef CUresult (*EncodeFn)(CUtensorMap*, CUtensorMapDataType, cuuint32_t, void*, const cuuint64_t*, const cuuint64_t*, const cuuint32_t*,
                             const cuuint32_t*, CUtensorMapInterleave, CUtensorMapSwizzle, CUtensorMapL2promotion, CUtensorMapFloatOOBfill);

bool encode(EncodeFn enc, CUtensorMap* m, const void* p, int rank, cuuint64_t d0, cuuint64_t d1, cuuint64_t d2, cuuint64_t s1, cuuint64_t s2,
            cuuint32_t b0, cuuint32_t b1, cuuint32_t b2) {
  cuuint64_t dims[3] = {d0, d1, d2}, strides[2] = {s1, s2};
  cuuint32_t box[3] = {b0, b1, b2}, es[3] = {1, 1, 1};
  return enc(m, CU_TENSOR_MAP_DATA_TYPE_BFLOAT16, rank, (void*)p, dims, strides, box, es, CU_TENSOR_MAP_INTERLEAVE_NONE, CU_TENSOR_MAP_SWIZZLE_128B,
             CU_TENSOR_MAP_L2_PROMOTION_L2_128B, CU_TENSOR_MAP_FLOAT_OOB_FILL_NONE) == CUDA_SUCCESS;
}

constexpr uint32_t job(int s) {
  const int after = s < 6 ? 12 + ((0x332110 >> (4 * s)) & 3) : s + 10;
  return (after & 7) | par(after) << 3 | (s & 7) << 4 | (s % 6) << 7 | partS(s) << 16 | tileS(s) << 18 | peerS(s) << 19;
}

}

extern "C" void kernel_launch(void* const* d_in, const int* in_sizes, int n_in, void* d_out, int out_size) {
  const __nv_bfloat16* x = (const __nv_bfloat16*)d_in[0];
  const __nv_bfloat16* wqkv = (const __nv_bfloat16*)d_in[1];
  const __nv_bfloat16* wo = (const __nv_bfloat16*)d_in[2];
  const __nv_bfloat16* w1 = (const __nv_bfloat16*)d_in[4];
  const __nv_bfloat16* b1 = (const __nv_bfloat16*)d_in[5];
  const __nv_bfloat16* w2 = (const __nv_bfloat16*)d_in[6];
  static EncodeFn enc = nullptr;
  if (!enc) {
    void* fn = nullptr;
    cudaDriverEntryPointQueryResult st;
    if (cudaGetDriverEntryPoint("cuTensorMapEncodeTiled", &fn, cudaEnableDefault, &st) != cudaSuccess || !fn) return;
    enc = (EncodeFn)fn;
    cudaFuncSetAttribute(fused_kernel, cudaFuncAttributeMaxDynamicSharedMemorySize, SMEM_BYTES);
  }
  Params prm;
  bool ok = true;
  ok &= encode(enc, &prm.map[0], wqkv, 2, D_, D_, 1, 3 * D_ * 2, 0, 64, 64, 1);
  ok &= encode(enc, &prm.map[1], w1, 2, F_, D_, 1, F_ * 2, 0, 64, 64, 1);
  ok &= encode(enc, &prm.map[2], w2, 3, 64, F_, 8, D_ * 2, 128, 64, 64, 2);
  ok &= encode(enc, &prm.map[3], w2, 3, 64, F_, 8, D_ * 2, 128, 64, 48, 2);
  ok &= encode(enc, &prm.map[4], wo, 3, 64, D_, 8, D_ * 2, 128, 64, 64, 2);
  ok &= encode(enc, &prm.map[5], x, 2, D_, S_, 1, D_ * 2, 0, 64, 128, 1);
  ok &= encode(enc, &prm.map[6], wqkv + D_, 3, D_, D_, 2, 3 * D_ * 2, D_ * 2, 64, 64, 2);
  ok &= encode(enc, &prm.map[7], d_out, 2, D_, S_, 1, D_ * 2, 0, 64, 16, 1);
  if (!ok) return;
  prm.zero = 0;
  for (int n = 0; n < 16; n++) prm.jobs[n] = job(2 * (n & 7) + (n >> 3));
  fused_kernel<<<128, 384, SMEM_BYTES>>>(prm, x, wqkv, wo, w1, b1, w2, (__nv_bfloat16*)d_out);
}
```
